```python
import torch

def _softmax(x, axis=-1):
    return torch.softmax(x, dim=axis)

def _gelu(x):
    return torch.nn.functional.gelu(x, approximate='tanh')

def _silu(x):
    return torch.nn.functional.silu(x)

def _sigmoid(x):
    return torch.sigmoid(x)

def _layernorm(x, axis=-1, eps=1e-05):
    m = x.mean(dim=axis, keepdim=True)
    v = x.var(dim=axis, keepdim=True, unbiased=False)
    return (x - m) / torch.sqrt(v + eps)

def _scatter_add(tgt, idx, src, axis=0):
    return tgt.clone().index_add_(axis, idx, src)

def _segment_sum(src, seg, n):
    out = torch.zeros((n,) + src.shape[1:], dtype=src.dtype)
    return out.index_add_(0, seg, src)

def _pad(x, pw):
    flat = tuple((v for pair in reversed(pw) for v in pair))
    return torch.nn.functional.pad(x, flat)
kernel_name = 'adaLN_cond__ssm_conv_s4d__glu_gated_glu__prompt'

def setup_inputs():

    _w = lambda a: (lambda t: t.to(torch.bfloat16) if t.is_floating_point() else t)(torch.as_tensor(a))

    def _A_setup():
        Bsz, L, D, N = (1, 2048, 640, 192)
        return {'u': _w((lambda *s: torch.randn(*s, dtype=torch.bfloat16) * 0.05)(Bsz, L, D)), 'log_A_real': _w((lambda *s: torch.randn(*s, dtype=torch.bfloat16) * 3.2)(D, N) * 0.5), 'A_imag': _w((lambda *s: torch.randn(*s, dtype=torch.bfloat16) * 0.1)(D, N) * 3.14), 'C_real': _w((lambda *s: torch.randn(*s, dtype=torch.bfloat16) * 0.4)(D, N) / N ** 0.5), 'C_imag': _w((lambda *s: torch.randn(*s, dtype=torch.bfloat16) * 0.4)(D, N) / N ** 0.5), 'log_dt': _w((lambda *s: torch.randn(*s, dtype=torch.bfloat16) * 0.1)(D) * 0.5 - 4.0), 'D_skip': _w((lambda *s: torch.randn(*s, dtype=torch.bfloat16) * 0.1)(D))}
    _A_in = _A_setup()

    def _B_setup():
        B, S, D, F = (1, 2048, 640, 1536)
        return {'x': _w((lambda *s: torch.randn(*s, dtype=torch.bfloat16) * 0.05)(B, S, D)), 'w_gate': _w((lambda *s: torch.randn(*s, dtype=torch.bfloat16) * 0.05)(D, F)), 'w_up': _w((lambda *s: torch.randn(*s, dtype=torch.bfloat16) * 0.05)(D, F)), 'w_down': _w((lambda *s: torch.randn(*s, dtype=torch.bfloat16) * 0.05)(F, D))}
    _B_in = _B_setup()
    return {'A_u': _A_in['u'], 'A_log_A_real': _A_in['log_A_real'], 'A_A_imag': _A_in['A_imag'], 'A_C_real': _A_in['C_real'], 'A_C_imag': _A_in['C_imag'], 'A_log_dt': _A_in['log_dt'], 'A_D_skip': _A_in['D_skip'], 'B_x': _B_in['x'], 'B_w_gate': _B_in['w_gate'], 'B_w_up': _B_in['w_up'], 'B_w_down': _B_in['w_down'], 'c': _w((lambda *s: torch.randn(*s, dtype=torch.bfloat16) * 0.1)(1, 640) * 8.0), 'w_mod': _w((lambda *s: torch.randn(*s, dtype=torch.bfloat16) * 0.1)(640, 6 * 640) * 640 ** (-0.5) * 8.0)}

def reference(A_u, A_log_A_real, A_A_imag, A_C_real, A_C_imag, A_log_dt, A_D_skip, B_x, B_w_gate, B_w_up, B_w_down, c, w_mod):

    def _A_ref(u, log_A_real, A_imag, C_real, C_imag, log_dt, D_skip):
        L = u.shape[1]
        dt = torch.exp(log_dt)
        A = -torch.exp(log_A_real) + 1j * A_imag
        C = (C_real + 1j * C_imag) * dt[:, None]
        pos = (lambda x, dt: x.to(dt))(torch.arange(L), log_dt.dtype)
        P = torch.exp((A * dt[:, None])[:, :, None] * pos[None, None, :])
        K = 2.0 * torch.einsum('dn,dnl->dl', C, P).real
        L2 = 2 * L
        u_t = (lambda x, *d: x.permute(*d))(u, 0, 2, 1)
        Kf = (lambda x, *a, **k: torch.fft.rfft(x.float(), *a, **k))(K, L2)
        Uf = (lambda x, *a, **k: torch.fft.rfft(x.float(), *a, **k))(u_t, L2)
        y = (lambda x, *a, **k: torch.fft.irfft(x, *a, **k).to(torch.bfloat16))(Uf * Kf[None, :, :], L2)[:, :, :L]
        y = (lambda x, *d: x.permute(*d))(y, 0, 2, 1)
        return y + u * D_skip[None, None, :]

    def _B_ref(x, w_gate, w_up, w_down):
        g = torch.einsum('bsd,df->bsf', x, w_gate)
        u = torch.einsum('bsd,df->bsf', x, w_up)
        h = _sigmoid(g) * u
        return torch.einsum('bsf,fd->bsd', h, w_down)
    x = A_u
    mod = (_silu(c) @ w_mod).reshape(c.shape[0], 6, 1, -1)
    sa, ca, ga, sb, cb, gb = (mod[:, 0].clone(), mod[:, 1].clone(), mod[:, 2].clone(), mod[:, 3].clone(), mod[:, 4].clone(), mod[:, 5].clone())
    h = _layernorm(x, axis=-1) * (1 + ca) + sa
    x = x + ga * _A_ref(h, A_log_A_real, A_A_imag, A_C_real, A_C_imag, A_log_dt, A_D_skip)
    h = _layernorm(x, axis=-1) * (1 + cb) + sb
    x = x + gb * _B_ref(h, B_w_gate, B_w_up, B_w_down)
    return x
```

```cpp
#include <cuda_runtime.h>
#include <cuda_bf16.h>
#include <cuda_fp16.h>
#include <cuda.h>
#include <stdint.h>
#define WPROM P256
#define WEARLY 0
#define XD 0
#define PERM 1

typedef __nv_bfloat16 bf16;
constexpr int L = 2048, D = 640, NM = 192, F = 1536;

__device__ __align__(128) unsigned g_modw[6 * D];
__device__ __align__(128) bf16 g_in[128 * D * 16];
__device__ __align__(128) unsigned short g_s1[128 * 48];
__device__ __align__(128) bf16 g_x2T[D * L];
__device__ __align__(128) bf16 g_aT[D * L];
__device__ uint4 g_hx[16 * 8 * 2 * 12 * 128];
__device__ uint4 g_v[2 * 3072];
__device__ uint4 g_st[L];
__device__ __align__(128) unsigned g_sync[128];
enum { C_EPOCH = 0, C_LN = 1, C_R = 2, C_X = 7, C_DONE = 32 };

#define TS(K, I) do {} while (0)
#define TSDUMP(K) do {} while (0)
#define TSINIT() do {} while (0)
#define TSW(I) do { if ((threadIdx.x & 127) == 0) TS(wg, I); } while (0)
__device__ __forceinline__ uint32_t s2u(const void* p) { return (uint32_t)__cvta_generic_to_shared(p); }
__device__ __forceinline__ float bflo(uint32_t v) { return __uint_as_float(v << 16); }
__device__ __forceinline__ float bfhi(uint32_t v) { return __uint_as_float(v & 0xffff0000u); }
__device__ __forceinline__ uint32_t pk(float lo, float hi) {
  uint32_t r; asm("cvt.rn.bf16x2.f32 %0, %1, %2;" : "=r"(r) : "f"(hi), "f"(lo)); return r;
}
__device__ __forceinline__ float rbf(float x) { return bflo(pk(x, x)); }
__device__ __forceinline__ uint32_t bmul(uint32_t a, uint32_t b) { uint32_t r; asm("mul.rn.bf16x2 %0, %1, %2;" : "=r"(r) : "r"(a), "r"(b)); return r; }
__device__ __forceinline__ uint32_t badd(uint32_t a, uint32_t b) { uint32_t r; asm("add.rn.bf16x2 %0, %1, %2;" : "=r"(r) : "r"(a), "r"(b)); return r; }
__device__ __forceinline__ uint32_t bfma(uint32_t a, uint32_t b, uint32_t c) { uint32_t r; asm("fma.rn.bf16x2 %0, %1, %2, %3;" : "=r"(r) : "r"(a), "r"(b), "r"(c)); return r; }
__device__ __forceinline__ uint32_t movm(uint32_t a) {
  uint32_t d; asm volatile("movmatrix.sync.aligned.m8n8.trans.b16 %0, %1;" : "=r"(d) : "r"(a)); return d;
}
__device__ __forceinline__ void bar_sync(int id, int n) { asm volatile("bar.sync %0, %1;" ::"r"(id), "r"(n) : "memory"); }
__device__ __forceinline__ void bar_arrive(int id, int n) { asm volatile("bar.arrive %0, %1;" ::"r"(id), "r"(n) : "memory"); }
__device__ __forceinline__ void mbar_init(uint32_t b, int c) { asm volatile("mbarrier.init.shared::cta.b64 [%0], %1;" ::"r"(b), "r"(c) : "memory"); }
__device__ __forceinline__ void mbar_expect(uint32_t b, int bytes) {
  asm volatile("mbarrier.arrive.expect_tx.shared::cta.b64 _, [%0], %1;" ::"r"(b), "r"(bytes) : "memory");
}
__device__ __forceinline__ void mbar_arrive(uint32_t b) { asm volatile("mbarrier.arrive.shared::cta.b64 _, [%0];" ::"r"(b) : "memory"); }
__device__ __forceinline__ void mbar_wait(uint32_t b, int ph) {
  asm volatile("{\n.reg .pred p;\nLW:\nmbarrier.try_wait.parity.shared::cta.b64 p, [%0], %1;\n@p bra LD;\nbra LW;\nLD:\n}" ::"r"(b), "r"(ph) : "memory");
}
__device__ __forceinline__ void mbar_wait_cluster(uint32_t b, int ph) {
  asm volatile("{\n.reg .pred p;\nLW:\nmbarrier.try_wait.parity.relaxed.cluster.shared::cta.b64 p, [%0], %1;\n@p bra LD;\nbra LW;\nLD:\n}\nfence.acquire.sync_restrict::shared::cluster.cluster;" ::"r"(b), "r"(ph) : "memory");
}
__device__ __forceinline__ void h_fix(uint4* h, uint32_t par, const uint4* base, uint32_t off) {
  asm volatile("{\n.reg .pred p;\n.reg .u32 c, u;\n.reg .u64 a;\nsetp.ne.u32 p, %16, 0;\nvote.sync.ballot.b32 c, p, 0xffffffff;\nLW:\nxor.b32 %0, %0, c;\nxor.b32 %4, %4, c;\nxor.b32 %8, %8, c;\nxor.b32 %12, %12, c;\n"
               "lop3.b32 u, %0, %4, %8, 0xfe;\nlop3.b32 u, u, %12, 1, 0xa8;\nsetp.ne.u32 p, u, 0;\nvote.sync.any.pred p, p, 0xffffffff;\n@!p bra.uni LD;\n"
               "mad.wide.u32 a, %18, 16, %17;\nld.relaxed.gpu.global.v4.b32 {%0,%1,%2,%3}, [a];\nld.relaxed.gpu.global.v4.b32 {%4,%5,%6,%7}, [a+512];\n"
               "ld.relaxed.gpu.global.v4.b32 {%8,%9,%10,%11}, [a+1024];\nld.relaxed.gpu.global.v4.b32 {%12,%13,%14,%15}, [a+1536];\nbra.uni LW;\nLD:\n}"
               : "+r"(h[0].x), "+r"(h[0].y), "+r"(h[0].z), "+r"(h[0].w), "+r"(h[1].x), "+r"(h[1].y), "+r"(h[1].z), "+r"(h[1].w),
                 "+r"(h[2].x), "+r"(h[2].y), "+r"(h[2].z), "+r"(h[2].w), "+r"(h[3].x), "+r"(h[3].y), "+r"(h[3].z), "+r"(h[3].w)
               : "r"(par), "l"(base), "r"(off) : "memory");
}
template <int SH> __device__ __forceinline__ uint32_t poll(const void* f, unsigned msk, unsigned v) {
  uint32_t r;
  asm volatile("{\n.reg .pred p, q;\n.reg .u32 c, u;\nmov.u32 c, 0;\nLW:\nld.relaxed.gpu.global.u32 %0, [%1];\nshr.u32 u, %0, %4;\nand.b32 u, u, %2;\nsetp.eq.u32 p, u, %3;\n"
               "vote.sync.all.pred p, p, 0xffffffff;\n@p bra.uni LD;\nnanosleep.u32 40;\nadd.u32 c, c, 1;\nsetp.lt.u32 q, c, 4194304;\n@q bra.uni LW;\ntrap;\nLD:\n}"
               : "=r"(r) : "l"(f), "r"(msk), "r"(v), "n"(SH) : "memory");
  return r;
}
__device__ __forceinline__ void cnt_wait(const unsigned* f, unsigned v) { poll<0>(f, ~0u, v); asm volatile("fence.acquire.gpu;" ::: "memory"); }
__device__ __forceinline__ void par_wait(const void* f, unsigned par) { poll<0>(f, 1u, par); }
__device__ __forceinline__ uint32_t tag_wait(const unsigned* f, unsigned tag) { return poll<16>(f, ~0u, tag); }
__device__ __forceinline__ void cnt_arrive(unsigned* f) { asm volatile("red.release.gpu.global.add.u32 [%0], 1;" ::"l"(f) : "memory"); }
__device__ __forceinline__ void cnt_arrive_rlx(unsigned* f) { asm volatile("red.relaxed.gpu.global.add.u32 [%0], 1;" ::"l"(f) : "memory"); }
__device__ __forceinline__ uint32_t mapa(uint32_t a, uint32_t cta) {
  uint32_t r; asm("mapa.shared::cluster.u32 %0, %1, %2;" : "=r"(r) : "r"(a), "r"(cta)); return r;
}
__device__ __forceinline__ void tma3d_e(uint32_t dst, const CUtensorMap* tm, int x, int y, int z, uint32_t bar) {
  asm volatile("{\n.reg .pred p;\nelect.sync _|p, 0xffffffff;\n"
               "@p cp.async.bulk.tensor.3d.shared::cluster.global.mbarrier::complete_tx::bytes [%0], [%1, {%3,%4,%5}], [%2];\n}"
               ::"r"(dst), "l"(tm), "r"(bar), "r"(x), "r"(y), "r"(z) : "memory");
}
__device__ __forceinline__ void mbar_expect_e(uint32_t b, int bytes) {
  asm volatile("{\n.reg .pred p;\nelect.sync _|p, 0xffffffff;\n@p mbarrier.arrive.expect_tx.shared::cta.b64 _, [%0], %1;\n}" ::"r"(b), "r"(bytes) : "memory");
}
__device__ __forceinline__ void mbar_arrive_e(uint32_t b) {
  asm volatile("{\n.reg .pred p;\nelect.sync _|p, 0xffffffff;\n@p mbarrier.arrive.shared::cta.b64 _, [%0];\n}" ::"r"(b) : "memory");
}
__device__ __forceinline__ void bulk_g2s_e(uint32_t dst, const void* src, int bytes, uint32_t bar) {
  asm volatile("{\n.reg .pred p;\nelect.sync _|p, 0xffffffff;\n@p cp.async.bulk.shared::cluster.global.mbarrier::complete_tx::bytes [%0], [%1], %2, [%3];\n}"
               ::"r"(dst), "l"(src), "r"(bytes), "r"(bar) : "memory");
}
__device__ __forceinline__ void bulk_s2g_e(void* dst, uint32_t src, int bytes) {
  asm volatile("{\n.reg .pred p;\nelect.sync _|p, 0xffffffff;\n@p cp.async.bulk.global.shared::cta.bulk_group [%0], [%1], %2;\n}" ::"l"(dst), "r"(src), "r"(bytes) : "memory");
}
__device__ __forceinline__ void cnt_arrive_e(unsigned* f) {
  asm volatile("{\n.reg .pred p;\nelect.sync _|p, 0xffffffff;\n@p red.relaxed.gpu.global.add.u32 [%0], 1;\n}" ::"l"(f) : "memory");
}
__device__ __forceinline__ void flag_set_e(unsigned* f, unsigned v) {
  asm volatile("{\n.reg .pred p;\nelect.sync _|p, 0xffffffff;\n@p st.relaxed.gpu.global.u32 [%0], %1;\n}" ::"l"(f), "r"(v) : "memory");
}
__device__ __forceinline__ void l2pf_e(const void* p) {
  asm volatile("{\n.reg .pred p;\nelect.sync _|p, 0xffffffff;\n@p cp.async.bulk.prefetch.L2.global [%0], 15360;\n}" ::"l"(p) : "memory");
}
__device__ __forceinline__ void fence_gpu() { asm volatile("fence.release.gpu;" ::: "memory"); }
__device__ __forceinline__ void cp16(uint32_t dst, const void* src) { asm volatile("cp.async.cg.shared.global [%0], [%1], 16;" ::"r"(dst), "l"(src) : "memory"); }
__device__ __forceinline__ void cp_wait() { asm volatile("cp.async.wait_all;" ::: "memory"); }
__device__ __forceinline__ void bulk_commit() { asm volatile("cp.async.bulk.commit_group;" ::: "memory"); }
__device__ __forceinline__ void bulk_wait_read() { asm volatile("cp.async.bulk.wait_group.read 0;" ::: "memory"); }
__device__ __forceinline__ void bulk_wait() { asm volatile("cp.async.bulk.wait_group 0;" ::: "memory"); }
__device__ __forceinline__ uint32_t dlo(uint32_t addr, uint32_t lbo) { return ((addr & 0x3FFFF) >> 4) | ((lbo >> 4) << 16); }
#define dhi(sbo, mode) ((int)((unsigned)((sbo) >> 4) | ((unsigned)(mode) << 30)))
__device__ __forceinline__ int fresh_tid() { unsigned x; asm volatile("mov.u32 %0, %%tid.x;" : "=r"(x)); return __shfl_sync(~0u, x & 127, x & 31); }
#define IDS() const int tid = fresh_tid(), lane = tid & 31, g = lane >> 2, t = lane & 3; (void)g; (void)t
__device__ __forceinline__ void wg_fence() { asm volatile("wgmma.fence.sync.aligned;" ::: "memory"); }
__device__ __forceinline__ void wg_commit() { asm volatile("wgmma.commit_group.sync.aligned;" ::: "memory"); }
template <int N> __device__ __forceinline__ void wg_wait() { asm volatile("wgmma.wait_group.sync.aligned %0;" ::"n"(N) : "memory"); }
template <int N> __device__ __forceinline__ void reg_fence(float* d) {
#pragma unroll
  for (int i = 0; i < N; i++) asm volatile("" : "+f"(d[i]) :: "memory");
}
__device__ __forceinline__ void fence_async() { asm volatile("fence.proxy.async.shared::cta;" ::: "memory"); }
__device__ __forceinline__ void fence_async_g() { asm volatile("fence.proxy.async.global;" ::: "memory"); }
__device__ __forceinline__ uint32_t lds32(uint32_t a) { uint32_t v; asm volatile("ld.shared.b32 %0, [%1];" : "=r"(v) : "r"(a) : "memory"); return v; }
__device__ __forceinline__ float ldsf(uint32_t a) { return __uint_as_float(lds32(a)); }
__device__ __forceinline__ uint4 lds128(uint32_t a) {
  uint4 v; asm volatile("ld.shared.v4.b32 {%0,%1,%2,%3}, [%4];" : "=r"(v.x), "=r"(v.y), "=r"(v.z), "=r"(v.w) : "r"(a) : "memory"); return v;
}
__device__ __forceinline__ float4 lds128f(uint32_t a) {
  float4 v; asm volatile("ld.shared.v4.f32 {%0,%1,%2,%3}, [%4];" : "=f"(v.x), "=f"(v.y), "=f"(v.z), "=f"(v.w) : "r"(a) : "memory"); return v;
}
__device__ __forceinline__ float4 lds128f_nv(uint32_t a) {
  float4 v; asm("ld.shared.v4.f32 {%0,%1,%2,%3}, [%4];" : "=f"(v.x), "=f"(v.y), "=f"(v.z), "=f"(v.w) : "r"(a)); return v;
}
__device__ __forceinline__ float2 lds64f(uint32_t a) {
  float2 v; asm volatile("ld.shared.v2.f32 {%0,%1}, [%2];" : "=f"(v.x), "=f"(v.y) : "r"(a) : "memory"); return v;
}
__device__ __forceinline__ void sts32(uint32_t a, uint32_t v) { asm volatile("st.shared.b32 [%0], %1;" ::"r"(a), "r"(v) : "memory"); }
__device__ __forceinline__ void sts64f(uint32_t a, float x, float y) { asm volatile("st.shared.v2.f32 [%0], {%1,%2};" ::"r"(a), "f"(x), "f"(y) : "memory"); }
__device__ __forceinline__ void sts128(uint32_t a, uint32_t x, uint32_t y, uint32_t z, uint32_t w) {
  asm volatile("st.shared.v4.b32 [%0], {%1,%2,%3,%4};" ::"r"(a), "r"(x), "r"(y), "r"(z), "r"(w) : "memory");
}
__device__ __forceinline__ uint4 ldg_nc(const void* p) {
  uint4 v; asm volatile("ld.global.nc.L1::no_allocate.v4.b32 {%0,%1,%2,%3}, [%4];" : "=r"(v.x), "=r"(v.y), "=r"(v.z), "=r"(v.w) : "l"(p)); return v;
}
__device__ __forceinline__ uint4 ldg_cg(const void* p) {
  uint4 v; asm volatile("ld.relaxed.gpu.global.v4.b32 {%0,%1,%2,%3}, [%4];" : "=r"(v.x), "=r"(v.y), "=r"(v.z), "=r"(v.w) : "l"(p) : "memory"); return v;
}
__device__ __forceinline__ uint4 ldg128(const void* p) {
  uint4 v; asm volatile("ld.global.v4.b32 {%0,%1,%2,%3}, [%4];" : "=r"(v.x), "=r"(v.y), "=r"(v.z), "=r"(v.w) : "l"(p) : "memory"); return v;
}
__device__ __forceinline__ float ldg_cgf(const float* p) { float v; asm volatile("ld.global.cg.f32 %0, [%1];" : "=f"(v) : "l"(p) : "memory"); return v; }
__device__ __forceinline__ uint32_t ldg_cg16(const void* p) { uint32_t v; asm volatile("ld.global.cg.u16 %0, [%1];" : "=r"(v) : "l"(p) : "memory"); return v; }
__device__ __forceinline__ uint32_t ldg_cg32(const void* p) { uint32_t v; asm volatile("ld.global.cg.b32 %0, [%1];" : "=r"(v) : "l"(p) : "memory"); return v; }
__device__ __forceinline__ uint32_t ldg_nc32(const void* p) { uint32_t v; asm volatile("ld.global.nc.b32 %0, [%1];" : "=r"(v) : "l"(p)); return v; }
__device__ __forceinline__ uint32_t ldg_u16(const void* p) { uint32_t v; asm volatile("ld.global.nc.u16 %0, [%1];" : "=r"(v) : "l"(p)); return v; }
__device__ __forceinline__ void mma_bf(float* d, uint32_t a0, uint32_t a1, uint32_t a2, uint32_t a3, uint32_t b0, uint32_t b1) {
  asm volatile("mma.sync.aligned.m16n8k16.row.col.f32.bf16.bf16.f32 {%0,%1,%2,%3}, {%4,%5,%6,%7}, {%8,%9}, {%0,%1,%2,%3};"
               : "+f"(d[0]), "+f"(d[1]), "+f"(d[2]), "+f"(d[3]) : "r"(a0), "r"(a1), "r"(a2), "r"(a3), "r"(b0), "r"(b1));
}
__device__ __forceinline__ void mma_bf8(float* d, uint32_t a0, uint32_t a1, uint32_t b0) {
  asm volatile("mma.sync.aligned.m16n8k8.row.col.f32.bf16.bf16.f32 {%0,%1,%2,%3}, {%4,%5}, {%6}, {%0,%1,%2,%3};"
               : "+f"(d[0]), "+f"(d[1]), "+f"(d[2]), "+f"(d[3]) : "r"(a0), "r"(a1), "r"(b0));
}
__device__ __forceinline__ void tmapf_e(const CUtensorMap* tm, int x, int y, int z) {
  asm volatile("{\n.reg .pred p;\nelect.sync _|p, 0xffffffff;\n@p cp.async.bulk.prefetch.tensor.3d.L2.global [%0, {%1,%2,%3}];\n}" ::"l"(tm), "r"(x), "r"(y), "r"(z) : "memory");
}
__device__ __forceinline__ void mma_hf(float* d, const uint32_t* a, uint32_t b0, uint32_t b1) {
  asm volatile("mma.sync.aligned.m16n8k16.row.col.f32.f16.f16.f32 {%0,%1,%2,%3}, {%4,%5,%6,%7}, {%8,%9}, {%0,%1,%2,%3};"
               : "+f"(d[0]), "+f"(d[1]), "+f"(d[2]), "+f"(d[3]) : "r"(a[0]), "r"(a[1]), "r"(a[2]), "r"(a[3]), "r"(b0), "r"(b1));
}
__device__ __forceinline__ void ldsm4t(uint32_t* r, uint32_t a) {
  asm volatile("ldmatrix.sync.aligned.m8n8.x4.trans.shared.b16 {%0,%1,%2,%3}, [%4];" : "=r"(r[0]), "=r"(r[1]), "=r"(r[2]), "=r"(r[3]) : "r"(a) : "memory");
}
__device__ __forceinline__ void ldsm2t(uint32_t* r, uint32_t a) {
  asm volatile("ldmatrix.sync.aligned.m8n8.x2.trans.shared.b16 {%0,%1}, [%2];" : "=r"(r[0]), "=r"(r[1]) : "r"(a) : "memory");
}
__device__ __forceinline__ void stsm4(uint32_t a, uint32_t r0, uint32_t r1, uint32_t r2, uint32_t r3) {
  asm volatile("stmatrix.sync.aligned.m8n8.x4.shared.b16 [%0], {%1,%2,%3,%4};" ::"r"(a), "r"(r0), "r"(r1), "r"(r2), "r"(r3) : "memory");
}
__device__ __forceinline__ void stsm4t(uint32_t a, uint32_t r0, uint32_t r1, uint32_t r2, uint32_t r3) {
  asm volatile("stmatrix.sync.aligned.m8n8.x4.trans.shared.b16 [%0], {%1,%2,%3,%4};" ::"r"(a), "r"(r0), "r"(r1), "r"(r2), "r"(r3) : "memory");
}
__device__ __forceinline__ float tanh_ap(float s, float x) { float y; asm volatile("{\n.reg .f32 t;\nmul.f32 t, %1, %2;\ntanh.approx.f32 %0, t;\n}" : "=f"(y) : "f"(s), "f"(x)); return y; }
__device__ __forceinline__ float ex2(float x) { float y; asm("ex2.approx.ftz.f32 %0, %1;" : "=f"(y) : "f"(x)); return y; }
__device__ __forceinline__ float rcp_ap(float x) { float y; asm("rcp.approx.ftz.f32 %0, %1;" : "=f"(y) : "f"(x)); return y; }
__device__ __forceinline__ float silu(float x) { return x * rcp_ap(1.f + ex2(fminf(x * -1.4426950408889634f, 126.f))); }
__device__ __forceinline__ void unpack8(float* v, uint4 q) {
  v[0] = bflo(q.x); v[1] = bfhi(q.x); v[2] = bflo(q.y); v[3] = bfhi(q.y);
  v[4] = bflo(q.z); v[5] = bfhi(q.z); v[6] = bflo(q.w); v[7] = bfhi(q.w);
}

template <int HB> __device__ __forceinline__ void wg_rs64(float* d, uint32_t a0, uint32_t a1, uint32_t a2, uint32_t a3, uint32_t bl, int bo, int sd) {
  asm volatile("{\n.reg .pred p;\n.reg .b64 db;\nsetp.ne.b32 p, %38, 0;\nadd.s64 db, %36, %37;\n"
   "wgmma.mma_async.sync.aligned.m64n64k16.f32.bf16.bf16 {%0, %1, %2, %3, %4, %5, %6, %7, %8, %9, %10, %11, %12, %13, %14, %15, %16, %17, %18, %19, %20, %21, %22, %23, %24, %25, %26, %27, %28, %29, %30, %31}, {%32,%33,%34,%35}, db, p, 1, 1, 0;\n}"
   : "+f"(d[0]), "+f"(d[1]), "+f"(d[2]), "+f"(d[3]), "+f"(d[4]), "+f"(d[5]), "+f"(d[6]), "+f"(d[7]), "+f"(d[8]), "+f"(d[9]), "+f"(d[10]), "+f"(d[11]), "+f"(d[12]), "+f"(d[13]), "+f"(d[14]), "+f"(d[15]), "+f"(d[16]), "+f"(d[17]), "+f"(d[18]), "+f"(d[19]), "+f"(d[20]), "+f"(d[21]), "+f"(d[22]), "+f"(d[23]), "+f"(d[24]), "+f"(d[25]), "+f"(d[26]), "+f"(d[27]), "+f"(d[28]), "+f"(d[29]), "+f"(d[30]), "+f"(d[31]) : "r"(a0),"r"(a1),"r"(a2),"r"(a3),"l"((uint64_t)(uint32_t)HB << 32 | bl),"l"((long long)bo),"r"(sd));
}
template <int HB> __device__ __forceinline__ void wg_rs32(float* d, uint32_t a0, uint32_t a1, uint32_t a2, uint32_t a3, uint32_t bl, int bo, int sd) {
  asm volatile("{\n.reg .pred p;\n.reg .b64 db;\nsetp.ne.b32 p, %22, 0;\nadd.s64 db, %20, %21;\n"
   "wgmma.mma_async.sync.aligned.m64n32k16.f32.bf16.bf16 {%0, %1, %2, %3, %4, %5, %6, %7, %8, %9, %10, %11, %12, %13, %14, %15}, {%16,%17,%18,%19}, db, p, 1, 1, 0;\n}"
   : "+f"(d[0]), "+f"(d[1]), "+f"(d[2]), "+f"(d[3]), "+f"(d[4]), "+f"(d[5]), "+f"(d[6]), "+f"(d[7]), "+f"(d[8]), "+f"(d[9]), "+f"(d[10]), "+f"(d[11]), "+f"(d[12]), "+f"(d[13]), "+f"(d[14]), "+f"(d[15]) : "r"(a0),"r"(a1),"r"(a2),"r"(a3),"l"((uint64_t)(uint32_t)HB << 32 | bl),"l"((long long)bo),"r"(sd));
}
template <int HA, int HB> __device__ __forceinline__ void wg_ss128tt(float* d, uint32_t al, int ao, uint32_t bl, int bo, int sd) {
  asm volatile("{\n.reg .pred p;\n.reg .b64 da, db;\nsetp.ne.b32 p, %68, 0;\nadd.s64 da, %64, %65;\nadd.s64 db, %66, %67;\n"
   "wgmma.mma_async.sync.aligned.m64n128k16.f32.bf16.bf16 {%0, %1, %2, %3, %4, %5, %6, %7, %8, %9, %10, %11, %12, %13, %14, %15, %16, %17, %18, %19, %20, %21, %22, %23, %24, %25, %26, %27, %28, %29, %30, %31, %32, %33, %34, %35, %36, %37, %38, %39, %40, %41, %42, %43, %44, %45, %46, %47, %48, %49, %50, %51, %52, %53, %54, %55, %56, %57, %58, %59, %60, %61, %62, %63}, da, db, p, 1, 1, 1, 1;\n}"
   : "+f"(d[0]), "+f"(d[1]), "+f"(d[2]), "+f"(d[3]), "+f"(d[4]), "+f"(d[5]), "+f"(d[6]), "+f"(d[7]), "+f"(d[8]), "+f"(d[9]), "+f"(d[10]), "+f"(d[11]), "+f"(d[12]), "+f"(d[13]), "+f"(d[14]), "+f"(d[15]), "+f"(d[16]), "+f"(d[17]), "+f"(d[18]), "+f"(d[19]), "+f"(d[20]), "+f"(d[21]), "+f"(d[22]), "+f"(d[23]), "+f"(d[24]), "+f"(d[25]), "+f"(d[26]), "+f"(d[27]), "+f"(d[28]), "+f"(d[29]), "+f"(d[30]), "+f"(d[31]), "+f"(d[32]), "+f"(d[33]), "+f"(d[34]), "+f"(d[35]), "+f"(d[36]), "+f"(d[37]), "+f"(d[38]), "+f"(d[39]), "+f"(d[40]), "+f"(d[41]), "+f"(d[42]), "+f"(d[43]), "+f"(d[44]), "+f"(d[45]), "+f"(d[46]), "+f"(d[47]), "+f"(d[48]), "+f"(d[49]), "+f"(d[50]), "+f"(d[51]), "+f"(d[52]), "+f"(d[53]), "+f"(d[54]), "+f"(d[55]), "+f"(d[56]), "+f"(d[57]), "+f"(d[58]), "+f"(d[59]), "+f"(d[60]), "+f"(d[61]), "+f"(d[62]), "+f"(d[63]) : "l"((uint64_t)(uint32_t)HA << 32 | al),"l"((long long)ao),"l"((uint64_t)(uint32_t)HB << 32 | bl),"l"((long long)bo),"r"(sd));
}
template <int HB> __device__ __forceinline__ void wg_rs128(float* d, uint32_t a0, uint32_t a1, uint32_t a2, uint32_t a3, uint32_t bl, int bo, int sd) {
  asm volatile("{\n.reg .pred p;\n.reg .b64 db;\nsetp.ne.b32 p, %70, 0;\nadd.s64 db, %68, %69;\n"
   "wgmma.mma_async.sync.aligned.m64n128k16.f32.bf16.bf16 {%0, %1, %2, %3, %4, %5, %6, %7, %8, %9, %10, %11, %12, %13, %14, %15, %16, %17, %18, %19, %20, %21, %22, %23, %24, %25, %26, %27, %28, %29, %30, %31, %32, %33, %34, %35, %36, %37, %38, %39, %40, %41, %42, %43, %44, %45, %46, %47, %48, %49, %50, %51, %52, %53, %54, %55, %56, %57, %58, %59, %60, %61, %62, %63}, {%64,%65,%66,%67}, db, p, 1, 1, 0;\n}"
   : "+f"(d[0]), "+f"(d[1]), "+f"(d[2]), "+f"(d[3]), "+f"(d[4]), "+f"(d[5]), "+f"(d[6]), "+f"(d[7]), "+f"(d[8]), "+f"(d[9]), "+f"(d[10]), "+f"(d[11]), "+f"(d[12]), "+f"(d[13]), "+f"(d[14]), "+f"(d[15]), "+f"(d[16]), "+f"(d[17]), "+f"(d[18]), "+f"(d[19]), "+f"(d[20]), "+f"(d[21]), "+f"(d[22]), "+f"(d[23]), "+f"(d[24]), "+f"(d[25]), "+f"(d[26]), "+f"(d[27]), "+f"(d[28]), "+f"(d[29]), "+f"(d[30]), "+f"(d[31]), "+f"(d[32]), "+f"(d[33]), "+f"(d[34]), "+f"(d[35]), "+f"(d[36]), "+f"(d[37]), "+f"(d[38]), "+f"(d[39]), "+f"(d[40]), "+f"(d[41]), "+f"(d[42]), "+f"(d[43]), "+f"(d[44]), "+f"(d[45]), "+f"(d[46]), "+f"(d[47]), "+f"(d[48]), "+f"(d[49]), "+f"(d[50]), "+f"(d[51]), "+f"(d[52]), "+f"(d[53]), "+f"(d[54]), "+f"(d[55]), "+f"(d[56]), "+f"(d[57]), "+f"(d[58]), "+f"(d[59]), "+f"(d[60]), "+f"(d[61]), "+f"(d[62]), "+f"(d[63]) : "r"(a0),"r"(a1),"r"(a2),"r"(a3),"l"((uint64_t)(uint32_t)HB << 32 | bl),"l"((long long)bo),"r"(sd));
}
template <int HA, int HB> __device__ __forceinline__ void wg_ss8(float* d, uint32_t al, int ao, uint32_t bl, int bo, int sd) {
  asm volatile("{\n.reg .pred p;\n.reg .b64 da, db;\nsetp.ne.b32 p, %8, 0;\nadd.s64 da, %4, %5;\nadd.s64 db, %6, %7;\n"
   "wgmma.mma_async.sync.aligned.m64n8k16.f32.bf16.bf16 {%0, %1, %2, %3}, da, db, p, 1, 1, 1, 0;\n}"
   : "+f"(d[0]), "+f"(d[1]), "+f"(d[2]), "+f"(d[3]) : "l"((uint64_t)(uint32_t)HA << 32 | al),"l"((long long)ao),"l"((uint64_t)(uint32_t)HB << 32 | bl),"l"((long long)bo),"r"(sd));
}
template <int HB> __device__ __forceinline__ void wg_rs128t(float* d, uint32_t a0, uint32_t a1, uint32_t a2, uint32_t a3, uint32_t bl, int bo, int sd) {
  asm volatile("{\n.reg .pred p;\n.reg .b64 db;\nsetp.ne.b32 p, %70, 0;\nadd.s64 db, %68, %69;\n"
   "wgmma.mma_async.sync.aligned.m64n128k16.f32.bf16.bf16 {%0, %1, %2, %3, %4, %5, %6, %7, %8, %9, %10, %11, %12, %13, %14, %15, %16, %17, %18, %19, %20, %21, %22, %23, %24, %25, %26, %27, %28, %29, %30, %31, %32, %33, %34, %35, %36, %37, %38, %39, %40, %41, %42, %43, %44, %45, %46, %47, %48, %49, %50, %51, %52, %53, %54, %55, %56, %57, %58, %59, %60, %61, %62, %63}, {%64,%65,%66,%67}, db, p, 1, 1, 1;\n}"
   : "+f"(d[0]), "+f"(d[1]), "+f"(d[2]), "+f"(d[3]), "+f"(d[4]), "+f"(d[5]), "+f"(d[6]), "+f"(d[7]), "+f"(d[8]), "+f"(d[9]), "+f"(d[10]), "+f"(d[11]), "+f"(d[12]), "+f"(d[13]), "+f"(d[14]), "+f"(d[15]), "+f"(d[16]), "+f"(d[17]), "+f"(d[18]), "+f"(d[19]), "+f"(d[20]), "+f"(d[21]), "+f"(d[22]), "+f"(d[23]), "+f"(d[24]), "+f"(d[25]), "+f"(d[26]), "+f"(d[27]), "+f"(d[28]), "+f"(d[29]), "+f"(d[30]), "+f"(d[31]), "+f"(d[32]), "+f"(d[33]), "+f"(d[34]), "+f"(d[35]), "+f"(d[36]), "+f"(d[37]), "+f"(d[38]), "+f"(d[39]), "+f"(d[40]), "+f"(d[41]), "+f"(d[42]), "+f"(d[43]), "+f"(d[44]), "+f"(d[45]), "+f"(d[46]), "+f"(d[47]), "+f"(d[48]), "+f"(d[49]), "+f"(d[50]), "+f"(d[51]), "+f"(d[52]), "+f"(d[53]), "+f"(d[54]), "+f"(d[55]), "+f"(d[56]), "+f"(d[57]), "+f"(d[58]), "+f"(d[59]), "+f"(d[60]), "+f"(d[61]), "+f"(d[62]), "+f"(d[63]) : "r"(a0),"r"(a1),"r"(a2),"r"(a3),"l"((uint64_t)(uint32_t)HB << 32 | bl),"l"((long long)bo),"r"(sd));
}
template <int HB> __device__ __forceinline__ void wg_rs32t(float* d, uint32_t a0, uint32_t a1, uint32_t a2, uint32_t a3, uint32_t bl, int bo, int sd) {
  asm volatile("{\n.reg .pred p;\n.reg .b64 db;\nsetp.ne.b32 p, %22, 0;\nadd.s64 db, %20, %21;\n"
   "wgmma.mma_async.sync.aligned.m64n32k16.f32.bf16.bf16 {%0, %1, %2, %3, %4, %5, %6, %7, %8, %9, %10, %11, %12, %13, %14, %15}, {%16,%17,%18,%19}, db, p, 1, 1, 1;\n}"
   : "+f"(d[0]), "+f"(d[1]), "+f"(d[2]), "+f"(d[3]), "+f"(d[4]), "+f"(d[5]), "+f"(d[6]), "+f"(d[7]), "+f"(d[8]), "+f"(d[9]), "+f"(d[10]), "+f"(d[11]), "+f"(d[12]), "+f"(d[13]), "+f"(d[14]), "+f"(d[15]) : "r"(a0),"r"(a1),"r"(a2),"r"(a3),"l"((uint64_t)(uint32_t)HB << 32 | bl),"l"((long long)bo),"r"(sd));
}

constexpr int STG = 65536;
constexpr int SM_TOTAL = 232448;
constexpr int KPB = 4288, KTP = KPB + 1792;
constexpr int O_KT = 2 * STG;
constexpr int O_H = O_KT + 5 * KTP;
constexpr int HP = 2496;
constexpr int O_WGA = O_H + 5 * 2 * HP;
constexpr int WGA = 13568, YP = 2112;
constexpr int O_XB = STG, O_S1 = O_XB + 20480, O_V4 = O_S1;
constexpr int O_X2 = 3 * STG;
constexpr int O_MISC = SM_TOTAL - 5120;
constexpr int O_BAR = O_MISC;
constexpr int B_FULL = 0, B_EMPTY = 24, B_FREE = 48, B_RECV = 56, B_WMOD = 72, B_SIDE = 80, B_X2 = 88, B_IN = 96, B_AE = 104, B_WF = 120, B_HF = 144, B_HE = 192, B_EPOCH = 240, B_XR = 5008;
constexpr int O_VT = O_MISC + 256;
constexpr int O_SILU = O_VT + 1536;
constexpr int O_ST = O_VT + 3072;
constexpr int O_VX = O_X2 + 24576;
constexpr int O_GB = O_ST + 1024;
constexpr int O_TS = O_GB + 192;
constexpr int KSCR = 7168;
static_assert(O_WGA + 3 * WGA <= O_MISC, "smem");
enum { NB_WG = 1, NB_X = 4, NB_KG = 5, NB_TOK = 6, NB_FRONT = 10, NB_STAG = 11, NB_SIDE = 12, NB_STG = 13, NB_INIT = 14, NB_SIG = 0, NB_F2 = 15 };

struct cf { float r, i; };
__device__ __forceinline__ cf cmul(cf a, cf b) { cf o; o.r = a.r * b.r - a.i * b.i; o.i = a.r * b.i + a.i * b.r; return o; }
__device__ __forceinline__ cf csq(cf a) { cf o; o.r = a.r * a.r - a.i * a.i; o.i = (a.r + a.r) * a.i; return o; }
__device__ __forceinline__ cf cexpa(float er, float rev) {
  const float m = ex2(er), r = (rev - rintf(rev)) * 6.283185307179586f;
  cf o; o.r = m * __cosf(r); o.i = m * __sinf(r); return o;
}
struct h2c { __half2 r, i; };
__device__ __forceinline__ h2c dup(cf q) { const __half2 p = __floats2half2_rn(q.r, q.i); h2c o; o.r = __low2half2(p); o.i = __high2half2(p); return o; }
__device__ __forceinline__ h2c hmulc(h2c p, h2c q) {
  h2c o;
  o.r = __hfma2(__hneg2(p.i), q.i, __hmul2(p.r, q.r));
  o.i = __hfma2(p.r, q.i, __hmul2(p.i, q.r));
  return o;
}
__device__ __forceinline__ h2c hmulcc(h2c p, h2c q) {
  h2c o;
  o.r = __hfma2(p.i, q.i, __hmul2(p.r, q.r));
  o.i = __hfma2(__hneg2(p.r), q.i, __hmul2(p.i, q.r));
  return o;
}
__device__ __forceinline__ uint32_t h2u(__half2 h) { return *(uint32_t*)&h; }
__device__ __forceinline__ void st4(uint32_t a, const h2c& p0, const h2c& p1, const h2c& p2, const h2c& p3) {
  sts128(a, h2u(p0.r), h2u(p1.r), h2u(p2.r), h2u(p3.r));
  sts128(a + 8 * 112, h2u(p0.i), h2u(p1.i), h2u(p2.i), h2u(p3.i));
}

__device__ __forceinline__ void stg128s(void* p, uint4 v) { asm volatile("st.relaxed.gpu.global.v4.b32 [%0], {%1,%2,%3,%4};" ::"l"(p), "r"(v.x), "r"(v.y), "r"(v.z), "r"(v.w) : "memory"); }
__device__ __forceinline__ void lim(int it) { asm volatile("{\n.reg .pred p;\nsetp.lt.s32 p, %0, 1048576;\n@p bra LK;\ntrap;\nLK:\n}" ::"r"(it)); }
__device__ __forceinline__ void stg128(void* p, uint4 v) { asm volatile("st.global.v4.b32 [%0], {%1,%2,%3,%4};" ::"l"(p), "r"(v.x), "r"(v.y), "r"(v.z), "r"(v.w) : "memory"); }

__device__ __forceinline__ void conv_epi_b(uint32_t sb, int wg, int tid, int r, int d, uint4 x0, uint4 x1, uint32_t ga, uint32_t opcb) {
  const uint32_t yb = sb + O_WGA + wg * WGA;
  const uint32_t ya = yb + (tid & 1) * YP + (tid >> 1) * 16;
  uint4 p0[2], p1[2];
  bar_sync(NB_WG + wg, 128);
#pragma unroll
  for (int hf = 0; hf < 2; hf++) { p0[hf] = lds128(ya + hf * 1024); p1[hf] = lds128(ya + 2 * YP + hf * 1024); }
#pragma unroll
  for (int hf = 0; hf < 2; hf++) {
    const uint4 x = hf ? x1 : x0;
    const uint32_t pa[4] = {p0[hf].x, p0[hf].y, p0[hf].z, p0[hf].w}, pb[4] = {p1[hf].x, p1[hf].y, p1[hf].z, p1[hf].w};
    const uint32_t xx[4] = {x.x, x.y, x.z, x.w};
    uint32_t xo[4];
#pragma unroll
    for (int e = 0; e < 4; e++) xo[e] = badd(xx[e], bmul(ga, badd(pa[e], pb[e])));
    stg128(g_aT + (size_t)d * L + 8 * tid + 1024 * hf, make_uint4(bmul(xo[0], opcb), bmul(xo[1], opcb), bmul(xo[2], opcb), bmul(xo[3], opcb)));
    stg128(g_x2T + (size_t)d * L + 8 * tid + 1024 * hf, make_uint4(xo[0], xo[1], xo[2], xo[3]));
  }
}
template <int N> __device__ __forceinline__ void xstep(float* a, int ln) {
#pragma unroll
  for (int e = 0; e < N; e++) {
    float k, x;
    asm("{\n.reg .pred p;\nsetp.ne.b32 p, %4, 0;\nselp.f32 %0, %3, %2, p;\nselp.f32 %1, %2, %3, p;\n}" : "=f"(k), "=f"(x) : "f"(a[e]), "f"(a[N + e]), "r"(ln & (2 * N)));
    a[e] = k + __shfl_xor_sync(~0u, x, 2 * N);
  }
}
__device__ __forceinline__ float xreduce16(float* a, int ln) { xstep<8>(a, ln); xstep<4>(a, ln); xstep<2>(a, ln); xstep<1>(a, ln); return a[0]; }
__device__ __forceinline__ void conv_signal(int r) { fence_gpu(); cnt_arrive_e(&g_sync[r]); }
__device__ __forceinline__ uint32_t bnorm(uint32_t x, uint32_t nm, uint32_t ih, uint32_t il) { const uint32_t c = badd(x, nm); return bfma(c, ih, bmul(c, il)); }
__device__ __forceinline__ float ln_den(float var) {
  float s; asm("sqrt.approx.ftz.f32 %0, %1;" : "=f"(s) : "f"(rbf(rbf(fmaxf(var, 0.f)) + 1e-5f)));
  return rbf(s);
}
struct Params {
  const bf16 *x, *logA, *Aim, *Cre, *Cim, *logdt, *Dsk, *wg, *wu, *wd, *c, *wmod;
  bf16* out;
  uint2 slot[12];
  uint4 job[16];
  unsigned char tile[64];
};

struct Maps { CUtensorMap m[13]; };
#define tmV2 MP.m[11]
#define tmD2 MP.m[9]
#define tmX2 MP.m[10]
#define tmV MP.m[7]
#define tmM MP.m[0]
#define tmA MP.m[1]
#define tmG MP.m[2]
#define tmU MP.m[3]
#define tmD MP.m[4]
#define tmX MP.m[5]
#define tmI MP.m[6]

__global__ void __cluster_dims__(2, 1, 1) __launch_bounds__(384, 1)
mega(const Params P, const __grid_constant__ Maps MP) {
  extern __shared__ __align__(1024) unsigned char smem[];
  const uint32_t sb = s2u(smem);
  const uint32_t bars = sb + O_BAR;
  const int cta = blockIdx.x;
  unsigned tx; asm volatile("mov.u32 %0, %%tid.x;" : "=r"(tx));
  const int wid = __shfl_sync(~0u, tx >> 5, 0), wg = wid >> 2;
  const int w = wid & 3;
  if (wid < 4) {
    asm volatile("{\n.reg .pred p;\nelect.sync _|p, 0xffffffff;\n@p mbarrier.init.shared::cta.b64 [%0], 1;\nfence.proxy.async.shared::cta;\n}" ::"r"(bars + B_XR + 8 * w) : "memory");
    mbar_expect_e(bars + B_XR + 8 * w, 5120);
  }
  const int nch = wg == 0 ? 1 : 2, r0 = wg == 0 ? 2 : wg - 1;
  const int dch = cta ^ ((cta >> 2) & 2);
  TSINIT();
  TSW(0);
#define ep1 lds32(bars + B_EPOCH)
#define TL ((int)P.tile[cta >> 1])
  uint32_t ldd;
  {
  const int tid = tx & 127, lane = tid & 31, g = lane >> 2, t = lane & 3;
  uint32_t pa[4], pb[4], ld0;
  {
    const unsigned wx = tx >> 5;
    const unsigned dk = dch + (wx < 4 ? 256 : 128 * ((wx >> 2) - 1 + 3 * ((wx >> 1) & 1)));
    const unsigned o = (dk * NM + (wx < 4 ? 64 * min(wx, 2u) : (wx & 1) * 96)) * 2 + lane * 4;
    const char* q0 = (const char*)P.logA + o; const char* q1 = (const char*)P.Aim + o; const char* q2 = (const char*)P.Cre + o; const char* q3 = (const char*)P.Cim + o;
    pa[0] = ldg_nc32(q0); pa[1] = ldg_nc32(q1); pa[2] = ldg_nc32(q2); pa[3] = ldg_nc32(q3);
    ld0 = ldg_u16(P.logdt + dk); ldd = ldg_u16(P.Dsk + dk);
    pb[0] = pb[1] = pb[2] = pb[3] = 0;
    if (wx >= 4 && lane < 16) { pb[0] = ldg_nc32(q0 + 128); pb[1] = ldg_nc32(q1 + 128); pb[2] = ldg_nc32(q2 + 128); pb[3] = ldg_nc32(q3 + 128); }
  }
  uint4 cv;
  if (tx < 96) cv = ldg_nc(P.c + 8 * min(tid, 79));
  if (wid < 4) {
    if (XD) __nanosleep(XD);
#pragma unroll
    for (int i = 0; i < 4; i++) bulk_g2s_e(sb + O_H + (4 * w + i) * 1296, P.x + (16 * cta + 4 * w + i) * D, 1280, bars + B_XR + 8 * w);
  }
  {
    const int b0 = wid + 6, c0 = wid == 4 ? 96 : (int)(0x111882101118ull >> (4 * wid)) & 15;
    asm volatile("{\n.reg .pred p, q;\nelect.sync _|p, 0xffffffff;\n@p mbarrier.init.shared::cta.b64 [%0], %1;\nsetp.ge.and.s32 q, %4, 6, p;\n@q mbarrier.init.shared::cta.b64 [%2], %3;\n"
                 "@p mbarrier.init.shared::cta.b64 [%0+96], %6;\n@p prefetch.tensormap [%5];\nfence.mbarrier_init.release.cluster;\n}"
                 ::"r"(bars + 8 * b0), "r"(c0), "r"(bars + 8 * (wid - 6)), "r"(wid >= 9 ? 8 : 1), "r"(wid), "l"(&tmM + wid + (wid == 11 && cta >= 48)), "r"(wid < 6 ? 1 : 4) : "memory");
    if (wid == 1 || wid == 2) mbar_expect_e(bars + 8 * b0, 128 * 80);
  }
  if (wg == 0) {
    unsigned e;
    asm volatile("ld.relaxed.gpu.global.u32 %0, [%1];" : "=r"(e) : "l"(&g_sync[C_EPOCH]) : "memory");
    if (w == 0 && cta < 120) asm volatile("st.relaxed.gpu.global.u32 [%0], %1;" ::"l"(&g_modw[32 * cta + lane]), "r"(0) : "memory");
    uint32_t so[5];
#pragma unroll
    for (int i = 0; i < 5; i++) {
      const int d = 160 * w + 32 * i + 8 * ((lane & 7) >> 1) + 2 * (lane >> 3) + (lane & 1), c = d & 127;
      so[i] = sb + O_KT + ((c ^ ((c >> 2) & 2)) * 5 + (d >> 7)) * 32 + (((lane ^ cta) >> 2) & 1) * 16;
    }
    uint4 xa[5], xb[5];
    mbar_wait(bars + B_XR + 8 * w, 0);
    if (w == 3 && cta < 120) tmapf_e(&tmM, 32 * cta, 0, 0);
    bar_sync(NB_WG, 128);
#pragma unroll
    for (int i = 0; i < 5; i++) { const uint32_t p = sb + O_H + g * 1296 + w * 320 + i * 64 + t * 16; xa[i] = lds128(p); xb[i] = lds128(p + 8 * 1296); }
    float sa[4] = {0.f, 0.f, 0.f, 0.f}, sc[4] = {0.f, 0.f, 0.f, 0.f}, q0[4] = {0.f, 0.f, 0.f, 0.f}, q1[4] = {0.f, 0.f, 0.f, 0.f}, q2[4] = {0.f, 0.f, 0.f, 0.f}, q3[4] = {0.f, 0.f, 0.f, 0.f};
    const uint32_t one = 0x3f803f80u;
#pragma unroll
    for (int i = 0; i < 5; i++) {
      stsm4t(so[i], xa[i].x, xa[i].y, xa[i].z, xa[i].w);
      stsm4t(so[i] ^ 16, xb[i].x, xb[i].y, xb[i].z, xb[i].w);
      mma_bf(sa, xa[i].x, xa[i].y, xa[i].z, xa[i].w, one, one);
      mma_bf(sc, xb[i].x, xb[i].y, xb[i].z, xb[i].w, one, one);
      mma_bf8(q0, xa[i].x, xa[i].y, xa[i].x); mma_bf8(q1, xa[i].x, xa[i].y, xa[i].y);
      mma_bf8(q2, xb[i].x, xb[i].y, xb[i].x); mma_bf8(q3, xb[i].x, xb[i].y, xb[i].y);
      mma_bf8(q0, xa[i].z, xa[i].w, xa[i].z); mma_bf8(q1, xa[i].z, xa[i].w, xa[i].w);
      mma_bf8(q2, xb[i].z, xb[i].w, xb[i].z); mma_bf8(q3, xb[i].z, xb[i].w, xb[i].w);
    }
    if (t == (g >> 1)) {
      sts64f(sb + O_VT + g * 48 + w * 8, sa[0] + sa[2], (g & 1) ? q0[1] + q1[3] : q0[0] + q1[2]);
      sts64f(sb + O_VT + (g + 8) * 48 + w * 8, sc[0] + sc[2], (g & 1) ? q2[1] + q3[3] : q2[0] + q3[2]);
    }
    fence_async();
    bar_sync(NB_WG, 128);
    TSW(1);
    if (w == 3) {
      bulk_s2g_e(g_in + (size_t)cta * (D * 16), sb + O_KT, 20480); bulk_commit();
      if (cta < 120) { mbar_expect_e(bars + B_WMOD, 40960); tma3d_e(sb, &tmM, 32 * cta, 0, 0, bars + B_WMOD); }
      sts32(bars + B_EPOCH, e + 1);
      {
        const int rr = lane & 15;
        const float4 v0 = lds128f(sb + O_VT + rr * 48), v1 = lds128f(sb + O_VT + rr * 48 + 16);
        const float mean = ((v0.x + v0.z) + (v1.x + v1.z)) * (1.f / D);
        const float inv = rcp_ap(ln_den(((v0.y + v0.w) + (v1.y + v1.w)) * (1.f / D) - mean * mean));
        const uint32_t p0 = pk(-mean, inv);
        unsigned short* gs = g_s1 + cta * 48 + (lane ^ ((cta & 4) << 1));
        gs[0] = lane < 16 ? p0 : p0 >> 16;
        if (lane < 16) gs[32] = pk(inv - bfhi(p0), 0.f);
      }
      bulk_wait();
#pragma unroll 1
      for (int q = 0; q < 5; q++) {
        const uint32_t kt = sb + O_KT + q * KTP, hz = sb + O_H + q * 2 * HP + 2048 + lane * 16;
        sts128(kt + KPB + (58 + lane) * 16, 0, 0, 0, 0);
        sts128(lane < 22 ? kt + KPB + (90 + lane) * 16 : (lane < 26 ? kt + (lane - 22) * 16 : kt + 64 + 4096 + (lane - 24) * 16), 0, 0, 0, 0);
        if (lane < 24) { sts128(hz, 0, 0, 0, 0); sts128(hz + HP, 0, 0, 0, 0); }
      }
      fence_async();
      bar_arrive(NB_STG, 288);
      fence_async_g(); conv_signal(C_LN); if (lane == 0) TS(3, 4);
    } else {
      if (tid < 80)
        sts128(sb + O_SILU + (tid < 40 ? tid * 32 : tid * 32 - 1264), pk(silu(bflo(cv.x)), silu(bfhi(cv.x))), pk(silu(bflo(cv.y)), silu(bfhi(cv.y))),
               pk(silu(bflo(cv.z)), silu(bfhi(cv.z))), pk(silu(bflo(cv.w)), silu(bfhi(cv.w))));
      __syncwarp();
    }
  }
  asm volatile("barrier.cluster.arrive.relaxed.aligned;" ::: "memory");
  TSW(2);
  if (wid != 3) {
    const uint32_t scr = sb + (wid < 4 ? 40960 + wid * KSCR : STG + (wid - 4) * KSCR);
    const float dt = rbf(ex2(bflo(ld0) * 1.4426950408889634f));
    const uint32_t m2 = __vmaxu2(__vmaxu2(pa[2] & 0x7fff7fffu, pa[3] & 0x7fff7fffu), __vmaxu2(pb[2] & 0x7fff7fffu, pb[3] & 0x7fff7fffu));
#pragma unroll
    for (int e = 0; e < 4; e++) pb[e] = __shfl_sync(~0u, pb[e], lane & 15);
    const uint32_t rot = lane < 16 ? 0x5432 : 0x7632;
    const uint32_t eb = min(max(__reduce_max_sync(~0u, max(m2 & 0xffffu, m2 >> 16)) >> 7, 1u), 253u);
    const float sdn = __uint_as_float((254u - eb) << 23);
    float acc[24];
#pragma unroll
    for (int i = 0; i < 24; i++) acc[i] = 0.f;
    const uint32_t row = scr + (16 * (lane >> 3) + (lane & 7)) * 112;
    const uint32_t aA = scr + ((lane & 7) + 8 * (lane >> 4)) * 112 + ((lane >> 3) & 1) * 16;
    const uint32_t aB = scr + ((lane & 7) + 8 * ((lane >> 3) & 1)) * 112 + 64 + (lane >> 4) * 16;
#pragma unroll 1
    for (int it = 0; it < (wg ? 3 : 2); it++) {
      {
      const float er = rbf(ex2(bflo(pa[0]) * 1.4426950408889634f)) * dt * -1.4426950408889634f;
      const float rv = bflo(pa[1]) * dt * 0.15915494309189535f;
      cf cc; cc.r = bflo(pa[2]) * sdn; cc.i = bflo(pa[3]) * sdn;
#pragma unroll
      for (int e = 0; e < 4; e++) pa[e] = __byte_perm(pa[e], pb[e], rot);
      const cf z = cexpa(er, rv), z32 = cexpa(32.f * er, 32.f * rv);
      const cf z2 = csq(z), z4 = csq(z2), z8 = csq(z4), z16 = csq(z8), z64 = csq(z32);
      const cf z128 = csq(z64), z256 = csq(z128), z512 = csq(z256);
      const cf c2 = cmul(cc, z2), c256 = cmul(cc, z256);
      {
        h2c v[16];
        v[0].r = __floats2half2_rn(1.f, z8.r); v[0].i = __floats2half2_rn(0.f, -z8.i);
        v[1] = hmulcc(v[0], dup(z16));
        const h2c q32 = dup(z32), q64 = dup(z64), q128 = dup(z128);
#pragma unroll
        for (int i = 0; i < 2; i++) v[2 + i] = hmulcc(v[i], q32);
        st4(row, v[0], v[1], v[2], v[3]);
#pragma unroll
        for (int i = 0; i < 4; i++) v[4 + i] = hmulcc(v[i], q64);
        st4(row + 16, v[4], v[5], v[6], v[7]);
#pragma unroll
        for (int i = 0; i < 8; i++) v[8 + i] = hmulcc(v[i], q128);
        st4(row + 32, v[8], v[9], v[10], v[11]);
        st4(row + 48, v[12], v[13], v[14], v[15]);
        const h2c q1 = dup(z), q4 = dup(z4), q256 = dup(z256), q512 = dup(z512);
        h2c a, b;
        a.r = __floats2half2_rn(cc.r, c2.r); a.i = __floats2half2_rn(cc.i, c2.i);
        b.r = __floats2half2_rn(cc.r, c256.r); b.i = __floats2half2_rn(cc.i, c256.i);
        const h2c a4 = hmulc(a, q4), b1 = hmulc(b, q512);
        st4(row + 64, a, a4, hmulc(a, q1), hmulc(a4, q1));
        st4(row + 80, hmulc(a, q256), hmulc(a4, q256), b1, hmulc(b1, q4));
        const h2c b2 = hmulc(b1, q512), b3 = hmulc(b2, q512), b4 = hmulc(b3, q512);
        st4(row + 96, b2, b3, b4, b1);
      }
      __syncwarp();
#pragma unroll
      for (int ks = 0; ks < 4; ks++) {
        uint32_t a0[4], a1[4], b[4], b2[2];
        ldsm4t(a0, aA + ks * 1792); ldsm4t(a1, aA + 32 + ks * 1792);
        ldsm4t(b, aB + ks * 1792); ldsm2t(b2, aB + 32 + ks * 1792);
        mma_hf(acc, a0, b[0], b[1]); mma_hf(acc + 4, a0, b[2], b[3]); mma_hf(acc + 8, a0, b2[0], b2[1]);
        mma_hf(acc + 12, a1, b[0], b[1]); mma_hf(acc + 16, a1, b[2], b[3]); mma_hf(acc + 20, a1, b2[0], b2[1]);
      }
      __syncwarp();
      if (wg == 2) TSW(it == 0 ? 1 : (it == 1 ? 3 : 6));
      }
    }
    {
      const float sup = __uint_as_float(eb << 23) * (2.f * dt);
      const float skip = lane == 0 && (w & 1) ? bflo(ldd) : 0.f;
      const uint32_t pb = sb + O_WGA + wg * WGA + w * 3136 + g * 96 + (g >> 2) * 16 + t * 8;
#pragma unroll
      for (int mt = 0; mt < 2; mt++)
#pragma unroll
        for (int n = 0; n < 3; n++) {
          sts64f(pb + mt * 1568 + n * 32, mt + n ? sup * acc[12 * mt + 4 * n] : fmaf(sup, acc[0], skip), sup * acc[12 * mt + 4 * n + 1]);
          sts64f(pb + mt * 1568 + 784 + n * 32, sup * acc[12 * mt + 4 * n + 2], sup * acc[12 * mt + 4 * n + 3]);
        }
    }
  }
  if (wg == 0) {
    fence_async();
    bar_sync(NB_WG, 128);
    TSW(3);
    if (cta < 120) {
      float va[4];
      const uint32_t dM = dlo(sb, 20480), dS = dlo(sb + O_SILU, 32);
      mbar_wait(bars + B_WMOD, 0);
      TSW(27);
#pragma unroll 1
      for (int k = 0; k < 20; k += 4) {
        wg_fence();
#pragma unroll
        for (int i = 0; i < 4; i++) wg_ss8<dhi(512, 2), 0>(va, dM + 64 * k, 64 * i, dS + 4 * k, 4 * i, k | i);
        wg_commit();
      }
      wg_wait<0>();
      reg_fence<4>(va);
      if (t == 0) { sts32(sb + O_VT + (16 * w + g) * 4, __float_as_uint(w < 2 ? va[0] : va[1])); sts32(sb + O_VT + (16 * w + g + 8) * 4, __float_as_uint(w < 2 ? va[2] : va[3])); }
      if (w == 0) {
        bar_sync(NB_X, 128);
        const float o = ldsf(sb + O_VT + lane * 4) + ldsf(sb + O_VT + 128 + lane * 4);
        const uint32_t v = badd(pk(o, o), (cta / 20 == 1 || cta / 20 == 4) ? 0x3f803f80u : 0u);
        asm volatile("st.relaxed.gpu.global.u32 [%0], %1;" ::"l"(&g_modw[32 * cta + lane]), "r"(__byte_perm(v, ep1 | 0x8000u, 0x5410)) : "memory");
      } else bar_arrive(NB_X, 128);
    }
    TSW(6);
    if (w == 3) bar_sync(NB_KG, 288);
  }
  }
  if (wg) { fence_async(); bar_arrive(NB_KG, 288); bar_sync(NB_STG, 288); }
  TSW(4);
  {
  IDS();
#pragma unroll 1
  for (int ch = 0; ch < nch; ch++) {
    const uint32_t kt = sb + O_KT + (r0 + 3 * ch) * KTP;
    float v[4] = {0.f, 0.f, 0.f, 0.f}, u[4] = {0.f, 0.f, 0.f, 0.f}, e0 = 0.f, e1 = 0.f, fa = 0.f, fb = 0.f;
    const uint32_t c1 = w == 0 ? 0 : (w == 1 ? 32 : 48);
    const uint32_t x0 = w == 1 ? 48 : (w == 2 ? 52 : 64);
    const uint32_t ro = (lane >> 3) * 784 + (lane & 7) * 96 + ((lane >> 2) & 1) * 16;
    const int l1 = lane | 1, l2 = (l1 + 1) & 31;
    const uint32_t f1 = (l1 >> 3) * 784 + (l1 & 7) * 96 + ((l1 >> 2) & 1) * 16 + 64 + 4 * w;
    const uint32_t f2 = (l2 >> 3) * 784 + (l2 & 7) * 96 + ((l2 >> 2) & 1) * 16 + 64 + 4 * w + (l2 ? 0 : 4);
    const uint32_t pb0 = sb + O_WGA + wg * WGA + ch * 6272;
#pragma unroll
    for (int p = 0; p < 3; p++) {
      if (p == 2 && wg) break;
      const uint32_t pb = pb0 + p * 3136;
      const float4 a = lds128f(pb + ro + c1);
      v[0] += a.x; v[1] += a.y; v[2] += a.z; v[3] += a.w;
      if (w == 0) { const float4 b = lds128f(pb + ro + 16); u[0] += b.x; u[1] += b.y; u[2] += b.z; u[3] += b.w; }
      e0 += ldsf(pb + x0); e1 += ldsf(pb + 3 * 784 + 7 * 96 + 16 + 28); fa += ldsf(pb + f1); fb += ldsf(pb + f2);
    }
    float k[9];
    if (w == 0) {
      const float pv = __shfl_up_sync(~0u, u[3], 1);
      k[0] = lane ? pv : 0.f; k[1] = v[0]; k[2] = u[0]; k[3] = v[1]; k[4] = u[1]; k[5] = v[2]; k[6] = u[2]; k[7] = v[3]; k[8] = u[3];
    } else if (w == 1) {
      const float nx = __shfl_down_sync(~0u, v[0], 1);
      k[0] = lane ? v[0] : e1; k[1] = v[0]; k[2] = v[0]; k[3] = v[1]; k[4] = v[2]; k[5] = v[2]; k[6] = v[2]; k[7] = v[3]; k[8] = lane < 31 ? nx : e0;
    } else {
      const float a = w == 2 ? v[0] : v[1], b = w == 2 ? v[2] : v[3];
      const float nx0 = __shfl_down_sync(~0u, a, 1), nx = lane < 31 ? nx0 : e0;
      k[0] = a; k[1] = a; k[2] = a; k[3] = a; k[4] = b; k[5] = b; k[6] = b; k[7] = nx; k[8] = nx;
    }
    sts128(kt + 64 + tid * 32, pk(k[1], k[0]), pk(k[2], k[1]), pk(k[3], k[2]), pk(k[4], k[3]));
    sts128(kt + 64 + tid * 32 + 16, pk(k[5], k[4]), pk(k[6], k[5]), pk(k[7], k[6]), pk(k[8], k[7]));
    if (tid == 96) {
      const uint32_t bb = pk(e0, e0);
      sts128(kt + 64 + 4096, bb, bb, bb, bb); sts128(kt + 64 + 4096 + 16, bb, bb & 0xffff0000u, 0, 0);
    }
    {
      const uint32_t kw = pk(fa, fb);
      const int n = 63 - 16 * w - (lane >> 1) - 4 * (lane & 1), s0 = 2 * (lane & 1);
      if (n >= 0) sts32(kt + KPB + n * 16 + s0 * 4, kw);
      if (n >= 2) sts32(kt + KPB + (n - 2) * 16 + s0 * 4 + 4, kw);
    }
  }
  TSW(5);
  fence_async();
  bar_sync(NB_WG + wg, 128);
  if (wg == 0) {
    if (w == 3) {
      const int j = (cta & 1) * 4 + (TL & 3);
      mbar_expect_e(bars + B_FULL, STG);
      tma3d_e(sb + 16384, &tmG, 0, 0, 3 * j, bars + B_FULL);
      tma3d_e(sb + 40960, &tmU, 0, 0, 3 * j, bars + B_FULL);
    }
    __syncwarp();
  }
  }
  TSW(7);
  uint4 x0, x1;
  uint32_t gav, opcb;
  int r = r0;
#pragma unroll 1
  for (int ch = 0;; ch++) {
    IDS();
    const int d = dch + 128 * r;
    const uint32_t hb = sb + O_H + r * 2 * HP;
    const uint32_t hsw = (cta & 16);
    const int c0 = w >> 1, irow = g + 8 * (w & 1);
    const uint32_t kt = sb + O_KT + r * KTP;
    const uint32_t kp = kt + (16 + irow + 16 * c0 - 2 * t) * 4;
    const uint32_t dH = dlo(hb, HP);
    float acc[64];
    uint32_t a[4][4], b[4][4];
#define LOAD_A(A, GRP)                                                               \
    _Pragma("unroll") for (int s = 0; s < 4; s++) {                                  \
      const uint32_t p = kp + (16 * (GRP) + 2 * s) * 64;                             \
      A[s][0] = lds32(p); A[s][1] = lds32(p + 512); A[s][2] = lds32(p - 32); A[s][3] = lds32(p + 480); \
    }
#define CONV3(A, DD, SD) _Pragma("unroll") for (int s = 0; s < 4; s++) {             \
      wg_rs64<8>(acc, A[s][0], A[s][1], A[s][2], A[s][3], dH, (DD) + 2 * s, SD);            \
      wg_rs32<8>(acc + 32, A[s][0], A[s][1], A[s][2], A[s][3], dH, (DD) + 64 + 2 * s, SD);  \
      wg_rs32<8>(acc + 48, A[s][0], A[s][1], A[s][2], A[s][3], dH, (DD) + 96 + 2 * s, SD);  \
    }
#define CONV2(A, DD) _Pragma("unroll") for (int s = 0; s < 4; s++) {                 \
      wg_rs64<8>(acc, A[s][0], A[s][1], A[s][2], A[s][3], dH, (DD) + 2 * s, 1);             \
      wg_rs32<8>(acc + 32, A[s][0], A[s][1], A[s][2], A[s][3], dH, (DD) + 64 + 2 * s, 1);   \
    }
    uint32_t c[4][4], e[4][4], f[1][4];
    if (ch && w == 3) { bar_sync(wg == 1 ? NB_SIG : NB_KG, 128); conv_signal(C_R + r - 3); if (lane == 0) TS(wg, 27); }
    LOAD_A(a, 0)
    LOAD_A(b, 1)
    LOAD_A(c, 2)
    LOAD_A(e, 3)
    { const uint32_t p = kp + 64 * 64; f[0][0] = lds32(p); f[0][1] = 0; f[0][2] = lds32(p - 32); f[0][3] = 0; }
    if (ch == 0) {
  if (wid == 9) {
          const unsigned e1 = ep1;
          cnt_wait(&g_sync[C_LN], e1 * 128);
          fence_async_g();
          mbar_expect_e(bars + B_IN, 20480 + 12288);
          tma3d_e(sb + O_XB, &tmI, cta * 80, 0, 0, bars + B_IN);
          bulk_g2s_e(sb + O_S1, g_s1, 12288, bars + B_IN);
          if ((threadIdx.x & 31) == 0) TS(3, 5);
          if (cta == 0) flag_set_e(&g_sync[C_EPOCH], e1);
        }
  if (wid == 9) {
    const uint32_t v = tag_wait(g_modw + ((lane & 3) == 3 ? 4 : (lane & 3)) * D + dch + 128 * min(lane >> 2, 4), (ep1 & 0x7fff) | 0x8000u);
    sts32(sb + O_ST + lane * 4, __byte_perm(v, 0, 0x1010));
    __syncwarp();
    mbar_arrive_e(bars + B_IN);
  }
      mbar_wait(bars + B_IN, 0);
      TSW(11);
    if (wid == 3 && cta < 96) {
      mbar_expect_e(bars + B_WMOD, 40960);
      tma3d_e(sb + STG + 32768, &tmV + (cta >= 48), 0, 320 * (cta & 1), (cta >> 1) % 24, bars + B_WMOD);
      tmapf_e(&tmV2 + (cta >= 48), 0, 320 * (cta & 1) + 256, (cta >> 1) % 24);
    }
      uint4 nm[2], ih[2], il[2];
#pragma unroll
      for (int hf = 0; hf < 2; hf++) { const uint32_t o = sb + O_S1 + tid * 96 + ((hf * 16) ^ ((tid & 4) << 2)); nm[hf] = lds128(o); ih[hf] = lds128(o + 32); il[hf] = lds128(o + 64); }
#pragma unroll 1
      for (int rr = r; rr < 4 + (wg >> 1); rr += 1 + 4 * (wg & 1) + wg) {
        const uint4 sc = lds128(sb + O_ST + rr * 16);
#define AFF(X) badd(bmul(X, sc.y), sc.x)
#pragma unroll
        for (int hf = 0; hf < 2; hf++) {
          const uint4 x = lds128(sb + O_XB + rr * 32 + tid * 160 + ((hf * 16) ^ hsw ^ ((tid & 4) << 2)));
          sts128(sb + O_H + rr * 2 * HP + hf * HP + (127 - tid) * 16, AFF(bnorm(x.x, nm[hf].x, ih[hf].x, il[hf].x)), AFF(bnorm(x.y, nm[hf].y, ih[hf].y, il[hf].y)),
                 AFF(bnorm(x.z, nm[hf].z, ih[hf].z, il[hf].z)), AFF(bnorm(x.w, nm[hf].w, ih[hf].w, il[hf].w)));
        }
      }
      fence_async();
      if (wg == 1) bar_arrive(NB_F2, 256);
      if (wg) bar_sync(NB_WG + wg, 128); else bar_sync(NB_F2, 256);
#pragma unroll 1
      for (int rr = r; rr < 4 + (wg >> 1); rr += 1 + 4 * (wg & 1) + wg) {
        const uint32_t hb = sb + O_H + rr * 2 * HP, pbb = sb + O_WGA + (rr < 3 ? wg * WGA : (rr - 2) * WGA + 4 * YP);
    {
      float hv[32];
#pragma unroll
      for (int cc = 0; cc < 4; cc++) {
        const int c8 = tid - 3 + cc;
        unpack8(hv + 8 * cc, lds128(hb + (c8 & 1) * HP + (127 - (c8 >> 1)) * 16));
      }
      float s7 = ((hv[13] + hv[14]) + (hv[15] + hv[16])) + ((hv[17] + hv[18]) + hv[19]);
      float s9 = ((hv[4] + hv[5]) + (hv[6] + hv[7])) + ((hv[8] + hv[9]) + (hv[10] + hv[11])) + hv[12];
      uint32_t o[8];
#pragma unroll
      for (int q = 0; q < 8; q++) {
        o[q] = pk(s7, s9);
        if (q < 7) { s7 += hv[20 + q] - hv[13 + q]; s9 += hv[13 + q] - hv[4 + q]; }
      }
      const uint32_t p = pbb + (8 * tid + 8 * (tid >> 2)) * 4;
      sts128(p, o[0], o[1], o[2], o[3]); sts128(p + 16, o[4], o[5], o[6], o[7]);
    }
      }
    }
      if (wid < 3) {
        const int q = min(tid, 79);
        const unsigned* ps = g_modw + (3 + (q & 1)) * D + 320 * (cta & 1) + 8 * (q >> 1);
        uint4 s0, s1; int it = 0; const uint32_t tg = (ep1 << 16) | 0x80000000u;
        do { s0 = ldg_cg(ps); s1 = ldg_cg(ps + 4); } while (__any_sync(~0u, ((s0.x ^ tg) | (s0.y ^ tg) | (s0.z ^ tg) | (s0.w ^ tg) | (s1.x ^ tg) | (s1.y ^ tg) | (s1.z ^ tg) | (s1.w ^ tg)) >> 16) && ++it < (1 << 20));
        sts128(sb + O_SILU + q * 16, __byte_perm(s0.x, s0.y, 0x5410), __byte_perm(s0.z, s0.w, 0x5410), __byte_perm(s1.x, s1.y, 0x5410), __byte_perm(s1.z, s1.w, 0x5410));
        fence_async();
      }
    if (r > 0) bar_sync(NB_TOK + r - 1, 256); else bar_sync(NB_WG + wg, 128);
    TSW(8 + 4 * ch);
    if (wid == 3 && cta < 96)
      tma3d_e(sb + O_V4, &tmV2 + (cta >= 48), 0, 320 * (cta & 1) + 256, (cta >> 1) % 24, bars + B_WMOD);
    wg_fence();
    CONV3(a, 0, s > 0)
    wg_commit();
    CONV3(b, 16, 1)
    CONV2(c, 32)
    wg_commit();
    wg_wait<1>();
    {
      const uint32_t pbb = sb + O_WGA + wg * WGA + ch * 4 * YP;
#pragma unroll
      for (int s = 0; s < 2; s++) {
        const int x2 = irow + 16 * (c0 + 2 * t) + 512 * s;
        const uint32_t q = pbb + (x2 + 8 * (x2 >> 5)) * 4;
        a[s][0] = lds32(q); a[s][1] = lds32(q + 160 * 4); a[s][2] = lds32(q + 320 * 4); a[s][3] = lds32(q + 480 * 4);
      }
    }
    CONV2(e, 48)
    if (r != 2 && r < 4) bar_arrive(NB_TOK + r, 256);
    {
      const uint32_t dE = dlo(kt + KPB, 256);
      wg_fence();
      wg_rs64<8>(acc, f[0][0], f[0][1], f[0][2], f[0][3], dH, 64, 1);
      wg_rs64<8>(acc, a[0][0], a[0][1], a[0][2], a[0][3], dE, 0, 1);
      wg_rs64<8>(acc, a[1][0], a[1][1], a[1][2], a[1][3], dE, 32, 1);
      wg_commit();
    }
    float va[4];
    if (r == 2) {
      if (cta < 96) {
        mbar_wait(bars + B_WMOD, 1);
        const uint32_t dT = dlo(sb + O_SILU, 32);
#pragma unroll 1
        for (int k = 0; k < 5; k++) {
          const uint32_t dA = dlo(sb + (k < 4 ? STG + 32768 + k * 8192 : O_V4), 16);
          wg_fence();
#pragma unroll
          for (int i = 0; i < 4; i++) wg_ss8<dhi(1024, 1), 0>(va, dA, 128 * i, dT + 16 * k, 4 * i, k | i);
          wg_commit();
        }
      }
      bar_arrive(NB_TOK + 2, 256);
    }
    { const uint4 sc = lds128(sb + O_ST + r * 16); gav = sc.z; opcb = sc.w; }
    { const uint32_t xo = sb + O_XB + r * 32 + (tid >> 1) * 160 + (((tid & 1) << 4) ^ hsw ^ ((tid & 8) << 1)); x0 = lds128(xo); x1 = lds128(xo + 64 * 160); }
    bar_sync(NB_WG + wg, 128);
    wg_wait<0>();
    reg_fence<64>(acc);
    TSW(9 + 4 * ch);
    if (r == 2 && cta < 96) {
      reg_fence<4>(va);
      const float v2 = __shfl_sync(~0u, va[2], lane & ~3), v1 = __shfl_sync(~0u, va[3], lane & ~3);
      const float a2 = t ? v2 : va[0], a1 = t ? v1 : va[1];
      if (t < 2) stg128s(g_v + (cta & 1) * 3072 + (cta >> 1) * 64 + 16 * w + 8 * t + g, make_uint4(pk(a1, a1 - rbf(a1)), pk(a2, a2 - rbf(a2)), ep1, 0));
    }
    {
      const uint32_t yw = sb + O_WGA + wg * WGA + w * YP;
#pragma unroll
      for (int q = 0; q < 4; q++) {
        uint32_t p[4];
#pragma unroll
        for (int e = 0; e < 4; e++) {
          const int jb = 4 * q + e;
          p[e] = jb < 15 ? pk(acc[4 * jb] + acc[(4 * jb + 6) & 63], acc[4 * jb + 1] + acc[(4 * jb + 7) & 63]) : pk(acc[60], acc[61]);
        }
        stsm4t(yw + (127 - lane + c0) * 16 - q * 512, p[0], p[1], p[2], p[3]);
      }
      if (c0 && lane == 0) sts128(yw, 0, 0, 0, 0);
    }
    if (r > 2) { asm volatile("" ::"r"(x0.x), "r"(x1.x)); bar_arrive(NB_X, 288); }
    conv_epi_b(sb, wg, tid, r, d, x0, x1, gav, opcb);
    if (r < 2 && w != 3) bar_arrive(wg == 1 ? NB_SIG : NB_KG, 128);
    TSW(10 + 4 * ch);
    if (r >= 2) break;
    r += 3;
  }

  if (wg == 0) {
    asm volatile("setmaxnreg.dec.sync.aligned.u32 40;");
    if (w == 0) {
      cnt_wait(&g_sync[C_R], ep1 * 128);
      fence_async_g();
      tma3d_e(sb, &tmA, 0, 0, 2 * (TL >> 2), bars + B_FULL);
      TSW(15);
    }
    if (w == 3) { bar_sync(NB_INIT, 128); conv_signal(C_R + 2); if ((threadIdx.x & 31) == 0) TS(0, 13); } else bar_arrive(NB_INIT, 128);
    const int m = TL >> 2, jq = TL & 3, rank = cta & 1, j = rank * 4 + jq;
#define ep ep1
    {
      if (w == 0) {
        bar_sync(NB_X, 288);
        mbar_expect_e(bars + B_FULL + 8, STG);
        tma3d_e(sb + STG, &tmA, 0, 64, 2 * m, bars + B_FULL + 8);
        tma3d_e(sb + STG + 16384, &tmG, 0, 64, 3 * j, bars + B_FULL + 8);
        tma3d_e(sb + STG + 40960, &tmU, 0, 64, 3 * j, bars + B_FULL + 8);
      }
      bar_sync(NB_FRONT, 384);
      fence_async();
      if (w == 3) conv_signal(C_R + 3);
    }
    TSW(14);
    if (w == 0) {
      int s = 2, ph = 1;
#pragma unroll 1
      for (int kb = 2; kb < 10; kb++) {
        const uint32_t st = sb + s * STG, fb = bars + B_FULL + 8 * s;
        if (kb == 3) l2pf_e(P.wd + cta * 7680);
        if (kb < 7 && !(kb & 1)) { cnt_wait(&g_sync[C_R + (kb >> 1)], ep * 128); fence_async_g(); }
        mbar_wait(bars + B_EMPTY + 8 * s, ph);
        if ((threadIdx.x & 31) == 0) TS(3, 14 + kb);
        mbar_expect_e(fb, STG);
        tma3d_e(st, &tmA, 0, 64 * kb, 2 * m, fb);
        tma3d_e(st + 16384, &tmG, 0, 64 * kb, 3 * j, fb);
        tma3d_e(st + 40960, &tmU, 0, 64 * kb, 3 * j, fb);
        if (++s == 3) { s = 0; ph ^= 1; }
      }
#pragma unroll 1
      for (int i = 0; i < 16; i++) {
        const uint4 jb = P.job[i];
        const uint32_t fb = bars + (jb.x >> 16);
        if (jb.y) {
          mbar_wait(bars + (jb.x & 0xff), (jb.x >> 8) & 1);
          mbar_expect_e(fb, jb.y);
        }
        const int k0 = 192 * (rank * 4 + ((jq + (jb.w >> 8)) & 3)) + (jb.w & 0xff);
        const uint32_t dm = jb.z & 0xffff, dx = jb.z >> 16;
        if (dm != 0xffff) {
          tma3d_e(sb + dm * 1024, &tmD, 0, k0, 2 * jq + rank, fb);
          tma3d_e(sb + dm * 1024 + 24576, &tmD, 0, k0, 2 * jq + (rank ^ 1), fb);
        }
        if (dx != 0xffff) tma3d_e(sb + dx * 1024, &tmD2, 0, k0, 16 + jq, fb);
      }
      mbar_expect_e(bars + B_X2, 20480);
      tma3d_e(sb + 2 * STG + 24576, &tmX, 0, 128 * jq + 64 * rank, 2 * m, bars + B_X2);
      tma3d_e(sb + 2 * STG + 49152, &tmX2, 0, 512 + 32 * jq + 16 * rank, 2 * m, bars + B_X2);
    } else {
      const int sw = w - 1, u = fresh_tid() - 32, ln = u & 31;
      float a[16];
      if (u < 48) stg128(g_hx + (m * 8 + j) * 3072 + (u >> 3) * 512 + 120 + (u & 7), make_uint4(~ep & 1, 0, 0, 0));
      __syncwarp();
      asm volatile("st.shared.b16 [%0], %1;" ::"r"(sb + O_GB + u * 2), "h"((unsigned short)tag_wait(
          g_modw + 5 * D + (u < 64 ? 128 * jq + 64 * rank + u : 512 + 32 * jq + 16 * rank + (u & 15)), (ep & 0x7fff) | 0x8000u)) : "memory");
#pragma unroll 1
      for (int q = 0; q < 2; q++) {
        const unsigned tg = ep;
        uint4 v0, v1, v2, v3; int it = 0;
        const uint4* pv = g_v + q * 1536 + 192 * j + u;
        do { v0 = ldg_cg(pv); v1 = ldg_cg(pv + 3072); v2 = ldg_cg(pv + 96); v3 = ldg_cg(pv + 3168); } while (__any_sync(~0u, (v0.z ^ tg) | (v1.z ^ tg) | (v2.z ^ tg) | (v3.z ^ tg)) && ++it < (1 << 20));
        sts128(sb + O_VX + (q * 64 + u + (u & 64)) * 16, v0.x, v0.y, v1.x, v1.y);
        sts128(sb + O_VX + (q * 64 + 96 + u + ((96 + u) & 192)) * 16, v2.x, v2.y, v3.x, v3.y);
      }
      __syncwarp();
      if (u == 0) TS(3, 3);
      cnt_wait(&g_sync[C_R + (ln & 3)], ep * 128);
      __syncwarp();
      {
        const bf16* xp = g_x2T + 128 * m + 16 * j + 8 * (u & 1);
#pragma unroll 1
        for (int i = u; i < 1280; i += 96) cp16(sb + O_X2 + i * 16, xp + (size_t)(i >> 1) * L);
      }
      if (u == 0) TS(3, 0);
      {
#pragma unroll
        for (int i = 0; i < 16; i++) a[i] = 0.f;
        cp_wait();
        uint4 nw = lds128(sb + O_X2 + u * 16);
#pragma unroll 1
        for (int i = 1; i < (sw ? 14 : 15); i++) {
          float v[8]; unpack8(v, nw);
          nw = lds128(sb + O_X2 + (u + 96 * i) * 16);
#pragma unroll
          for (int e = 0; e < 8; e++) { a[2 * e] += v[e]; a[2 * e + 1] = fmaf(v[e], v[e], a[2 * e + 1]); }
        }
        __syncwarp();
        sts32(sb + O_ST + sw * 128 + (ln & 1) * 64 + (ln >> 1) * 4, __float_as_uint(xreduce16(a, ln)));
        bar_sync(NB_SIDE, 96);
        if (sw == 1) {
          if (ln < 16) {
            const float2 p0 = lds64f(sb + O_ST + ln * 8), p1 = lds64f(sb + O_ST + 128 + ln * 8), p2 = lds64f(sb + O_ST + 256 + ln * 8);
            const float mean = (p0.x + p1.x + p2.x) * (1.f / D);
            const float den = ln_den((p0.y + p1.y + p2.y) * (1.f / D) - mean * mean);
            stg128s(g_st + 128 * m + 16 * j + ln, make_uint4(__float_as_uint(0.5f * rcp_ap(den)), pk(-mean, den), ep, 0));
          }
          __syncwarp();
        }
        bar_sync(NB_SIDE, 96);
      }
      if (u == 0) TS(3, 1);
      {
        const uint4* ps = g_st + 128 * m + u;
        uint4 v0, v1; int it = 0; const unsigned tg = ep;
        do { if (it) __nanosleep(60); v0 = ldg_cg(ps); v1 = ldg_cg(ps + 32); } while (__any_sync(~0u, (v0.z ^ tg) | (v1.z ^ tg)) && ++it < (1 << 20));
        sts64f(sb + O_ST + u * 8, __uint_as_float(v0.x), __uint_as_float(v0.y));
        sts64f(sb + O_ST + (u + 32) * 8, __uint_as_float(v1.x), __uint_as_float(v1.y));
      }
      fence_async();
      mbar_arrive(bars + B_SIDE);
      if (u == 0) TS(3, 2);
      if (sw < 2) {
        mbar_wait(bars + B_IN, 1);
#pragma unroll 1
        for (int i = 0; i < 9; i++) {
          const int th = i / 3, sl = i - 3 * th;
          const uint4* src = g_hx + ((m * 8 + rank * 4 + ((jq + sl + 1) & 3)) * 6 + sw * 3 + th) * 512;
          if (sl == 0) par_wait(g_hx + ((m * 8 + rank * 4 + ((jq + min(ln, 2) + 1) & 3)) * 6 + sw * 3 + th) * 512 + 120, ep & 1);
          if (ln == 0 && sl == 0) TS(0, 19 + 4 * sw + th);
          fence_async_g();
          const uint32_t bo = 24 * sw + 8 * sl;
          mbar_wait(bars + B_HE + bo, th & 1);
          mbar_expect_e(bars + B_HF + bo, 8192);
          bulk_g2s_e(sb + (sw ? 8192 + sl * 24576 : O_X2 + sl * 8192), src, 8192, bars + B_HF + bo);
        }
      }
    }
    __syncwarp();
    asm volatile("barrier.cluster.wait.aligned;" ::: "memory");
  } else {
    const uint32_t rank = cta & 1;
    const int m = TL >> 2, jq = TL & 3, j = rank * 4 + jq;
    const int cw = wg - 1;
    bar_arrive(NB_FRONT, 384);
    __syncwarp();
    asm volatile("barrier.cluster.wait.aligned;" ::: "memory");
    asm volatile("setmaxnreg.inc.sync.aligned.u32 232;");
    TSW(15);
    uint4 hA[12];
    float oc[80];
    IDS();
#define G2_MMA(H, N, SD)                                                                       \
    { const uint32_t dW = dlo(sb, 24576) + P.slot[N].x, dX = dlo(sb, 24576) + P.slot[N].y;   \
      wg_fence();                                                                              \
      _Pragma("unroll") for (int q = 0; q < 4; q++) {                                          \
        wg_rs128t<dhi(1024, 1)>(oc, (H)[q].x, (H)[q].y, (H)[q].z, (H)[q].w, dW, 128 * q, q ? 1 : (SD));       \
        wg_rs32t<dhi(512, 2)>(oc + 64, (H)[q].x, (H)[q].y, (H)[q].z, (H)[q].w, dX, 64 * q, q ? 1 : (SD)); \
      }                                                                                        \
      wg_commit(); wg_wait<1>(); }
    {
      float a0[64], a1[64], a2[64];
#define G1_K(ACC, AT, ST, SD)                                                                  \
      _Pragma("unroll") for (int kk = 0; kk < 4; kk++)                                         \
        wg_ss128tt<dhi(1024, 1), dhi(1024, 1)>(ACC, dA, (ST) * 4096 + 128 * kk, dG, (ST) * 4096 + (AT) * 512 + 128 * kk, kk ? 1 : (SD));
      int s = 0, ph = 0;
#pragma unroll 1
      for (int kb = 0; kb < 8; kb++) {
        mbar_wait(bars + B_FULL + 8 * s, ph);
        if (kb == 0) TSW(16);
        if (threadIdx.x == 128) TS(3, 6 + kb);
        const uint32_t dA = dlo(sb + s * STG + cw * 8192, 16), dG = dlo(sb + s * STG + 16384, 24576);
        wg_fence();
        G1_K(a0, 0, 0, kb)
        wg_commit();
        wg_wait<1>();
        if (kb > 0) mbar_arrive_e(bars + B_EMPTY + 8 * (s == 0 ? 2 : s - 1));
        wg_fence();
        G1_K(a1, 1, 0, kb) G1_K(a2, 2, 0, kb)
        wg_commit();
        if (++s == 3) { s = 0; ph ^= 1; }
      }
      const uint32_t dA = dlo(sb + cw * 8192, 16), dG = dlo(sb + 16384, 24576), dV = dlo(sb + O_VX, 0);
      mbar_wait(bars + B_FULL + 16, 0);
      if (cw) { wg_wait<0>(); mbar_arrive_e(bars + B_EMPTY + 8); bar_sync(NB_STAG, 256); }
      wg_fence();
      G1_K(a0, 0, 2, 1)
      wg_commit();
      mbar_wait(bars + B_SIDE, 0);
      const float2 st0 = lds64f(sb + O_ST + (64 * cw + 16 * w + g) * 8), st1 = lds64f(sb + O_ST + (64 * cw + 16 * w + g + 8) * 8);
      const uint32_t sel = (t & 1) ? 0x3232 : 0x1010;
      const uint32_t e0 = __byte_perm(__float_as_uint(st0.y), 0, sel), e1 = __byte_perm(__float_as_uint(st1.y), 0, sel);
      wg_wait<1>();
      if (cw == 0) { mbar_arrive_e(bars + B_EMPTY + 8); mbar_arrive_e(bars + B_HE); mbar_arrive_e(bars + B_HE + 8); mbar_arrive_e(bars + B_HE + 16); }
      mbar_wait(bars + B_FULL, 1);
      wg_fence();
      wg_rs128<8>(a0, e0, e1, 0, 0, dV, 0, 1);
      G1_K(a0, 0, 0, 1)
      wg_commit();
      if (cw == 0) bar_arrive(NB_STAG, 256);
      uint4* dst = g_hx + (m * 8 + j) * 3072 + cw * 1536 + w * 128 + lane;
      const uint32_t par = ep1 & 1;
#define EPI(ACC, TH)                                                                           \
      reg_fence<64>(ACC);                                                                      \
      _Pragma("unroll") for (int q = 0; q < 4; q++) {                                          \
        uint32_t hp[4];                                                                        \
        _Pragma("unroll") for (int e = 0; e < 4; e++) {                                        \
          const float rs = (e & 1) ? st1.x : st0.x;                                            \
          const float u0 = ACC[32 + 8 * q + 2 * e], u1 = ACC[33 + 8 * q + 2 * e];       \
          hp[e] = pk(fmaf(u0, tanh_ap(rs, ACC[8 * q + 2 * e]), u0), fmaf(u1, tanh_ap(rs, ACC[8 * q + 2 * e + 1]), u1)); \
        }                                                                                      \
        hA[4 * (TH) + q] = make_uint4((hp[0] & ~1u) | par, hp[1], hp[2], hp[3]);               \
        stg128(dst + (TH) * 512 + q * 32, hA[4 * (TH) + q]);                                   \
      }
#define ATOM(ACC, AT)                                                                          \
      wg_fence();                                                                              \
      wg_rs128<8>(ACC, e0, e1, 0, 0, dV, 128 * (AT), 1);                                       \
      G1_K(ACC, AT, 2, 1) G1_K(ACC, AT, 0, 1)                                                  \
      wg_commit();
      wg_wait<0>();
      TSW(17);
      mbar_arrive_e(bars + B_AE);
      EPI(a0, 0)
      if (w == 0) mbar_arrive_e(bars + B_IN);
      ATOM(a1, 1)
      wg_wait<0>();
      mbar_arrive_e(bars + B_AE + 8);
      EPI(a1, 1)
      ATOM(a2, 2)
      wg_wait<0>();
      TSW(18);
      mbar_arrive_e(bars + B_EMPTY + 16);
      if (cw == 0) bar_arrive(NB_F2, 256);
      else { bar_sync(NB_F2, 256); mbar_arrive_e(bars + B_HE + 24); mbar_arrive_e(bars + B_HE + 32); mbar_arrive_e(bars + B_HE + 40); }
      EPI(a2, 2)
    }
    TSW(19);
    const uint32_t par = lane ? 0 : ep1 & 1;
    const uint4* hsrc = g_hx + ((m * 8 + rank * 4) * 6 + cw * 3) * 512 + w * 128 + lane;
    const uint32_t hl = sb + (cw ? 8192 : O_X2) + w * 2048 + lane * 16, hst = cw ? 24576 : 8192;
#define G2_LD(B, TH)                                                                           \
      mbar_wait(bars + B_HF + 24 * cw + 8 * (B), (TH) & 1);                                    \
      _Pragma("unroll") for (int q = 0; q < 4; q++) hA[4 * (B) + q] = lds128(hl + (B) * hst + q * 512);
#define G2_FIX(B, TH)                                                                          \
      h_fix(hA + 4 * (B), par, hsrc, (((jq + (B) + 1) & 3) * 6 + (TH)) * 512);                 \
      if ((TH) >= 0) mbar_arrive_e(bars + B_HE + 24 * cw + 8 * (B));
#pragma unroll
    for (int q = 0; q < 4; q++) asm volatile("and.b32 %0, %0, -2;" : "+r"(hA[q].x) :: "memory");
#pragma unroll 1
    for (int i = 0;; i++) {
      if (i < 2) mbar_wait(bars + B_FULL + 8 + 8 * i, 1);
      if (i == 1) mbar_wait(bars + B_WF, 0);
      G2_MMA(hA, 3 * i, i)
      G2_FIX(1, i - 1)
      if (i == 1) mbar_arrive_e(bars + B_EMPTY + 8);
      if (i) { G2_LD(2, i - 1) }
      G2_MMA(hA + 4, 3 * i + 1, 1)
      G2_FIX(2, i - 1)
      if (i < 3) { G2_LD(0, i) }
      if (i) mbar_wait(bars + (i == 1 ? B_WF + 8 : B_FULL + 8 * (i - 1)), 0);
      G2_MMA(hA + 8, 3 * i + 2, 1)
      TSW(20 + i);
      if (i == 3) break;
      G2_FIX(0, i)
      if (i == 2) {
        mbar_arrive_e(bars + B_EMPTY + 16);
        asm volatile("{\n.reg .pred p;\nelect.sync _|p, 0xffffffff;\n@p mbarrier.arrive.relaxed.cluster.shared::cluster.b64 _, [%0];\n}" ::"r"(mapa(bars + B_FREE, rank ^ 1)) : "memory");
      }
      G2_LD(1, i)
    }
    uint32_t xr[20]; uint32_t gb[10];
    mbar_wait(bars + B_X2, 0);
    {
      const uint32_t xo = sb + 2 * STG + 24576 + (8 * (lane >> 4) + (lane & 7)) * 128 + (((2 * w + ((lane >> 3) & 1)) ^ (lane & 7)) << 4);
#pragma unroll
      for (int b = 0; b < 4; b++) ldsm4t(xr + 4 * b, xo + cw * 8192 + b * 2048);
      ldsm4t(xr + 16, xo + 24576 + cw * 2048);
    }
#pragma unroll
    for (int b = 0; b < 10; b++) gb[b] = lds32(sb + O_GB + (8 * b + 2 * t) * 2);
    uint32_t rh[2], rl[2];
#pragma unroll
    for (int e = 0; e < 2; e++) { const float rs = ldsf(sb + O_ST + (64 * cw + 16 * w + g + 8 * e) * 8); rh[e] = pk(rs, rs); const float lo = rs - bflo(rh[e]); rl[e] = pk(lo, lo); }
    const uint32_t ob = hl - lane * 16;
    uint32_t os = ob + (lane & 7) * 176 + ((lane >> 3) & 1) * hst + (lane >> 4) * 16;
    uint32_t oa = ob + (lane >> 3) * 176 + (lane & 7) * 16, oe = ob + ((lane >> 1) & 7) * 176 + (lane >> 4) * hst + 128 + (lane & 1) * 16;
    bf16* po = P.out + ((128 * m + 64 * cw + 16 * w + (lane >> 3)) * D + 128 * jq + 64 * rank + (lane & 7) * 8);
    bf16* pe = P.out + ((128 * m + 64 * cw + 16 * w + (lane >> 1)) * D + 512 + 32 * jq + 16 * rank + (lane & 1) * 8);
    asm volatile("" : "+r"(os), "+r"(oa), "+r"(oe), "+l"(po), "+l"(pe));
    mbar_wait_cluster(bars + B_FREE, 0);
    wg_wait<0>();
    reg_fence<80>(oc);
    TSW(24);
    const uint32_t xb = sb + 16384 + cw * 24576 + tid * 16;
    uint32_t op[40];
    {
      const uint32_t rb = mapa(xb, rank ^ 1), rbar = mapa(bars + B_RECV + 8 * cw, rank ^ 1);
#pragma unroll
      for (int e = 0; e < 40; e++) op[e] = pk(oc[2 * e], oc[2 * e + 1]);
#pragma unroll
      for (int e = 0; e < 4; e++) { const uint32_t lo = op[32 + e], hi = op[36 + e]; op[32 + e] = rank ? lo : hi; op[36 + e] = rank ? hi : lo; }
#pragma unroll
      for (int b = 0; b < 5; b++)
        asm volatile("st.async.shared::cluster.mbarrier::complete_tx::bytes.v4.b32 [%0], {%1,%2,%3,%4}, [%5];"
                     ::"r"(rb + b * 2048), "r"(op[16 + 4 * b]), "r"(op[17 + 4 * b]), "r"(op[18 + 4 * b]), "r"(op[19 + 4 * b]), "r"(rbar) : "memory");
    }
    mbar_wait_cluster(bars + B_RECV + 8 * cw, 0);
    TSW(25);
#pragma unroll
    for (int b = 0; b < 5; b++) {
      const uint4 q = lds128(xb + b * 2048);
      const uint32_t p[4] = {q.x, q.y, q.z, q.w};
#pragma unroll
      for (int e = 0; e < 4; e++) {
        xr[4 * b + e] = badd(xr[4 * b + e], bmul(gb[2 * b + (e >> 1)], bnorm(op[(b < 4 ? 4 * b : 36) + e], p[e], rh[e & 1], rl[e & 1])));
      }
    }
#pragma unroll
    for (int b = 0; b < 5; b++)
      stsm4(os + b * 32, xr[4 * b], xr[4 * b + 1], xr[4 * b + 2], xr[4 * b + 3]);
    __syncwarp();
#pragma unroll
    for (int i = 0; i < 4; i++) stg128(po + 4 * i * D, lds128(oa + ((i & 1) * 704 + (i >> 1) * hst)));
    stg128(pe, lds128(oe));
    TSW(26);
    if (tid == 0) { TSDUMP(wg); if (cw) { TSDUMP(3); TSDUMP(0); } }
  }
}

typedef CUresult (*EncFn)(CUtensorMap*, CUtensorMapDataType, cuuint32_t, void*, const cuuint64_t*, const cuuint64_t*, const cuuint32_t*,
                          const cuuint32_t*, CUtensorMapInterleave, CUtensorMapSwizzle, CUtensorMapL2promotion, CUtensorMapFloatOOBfill);

static void make_map(EncFn enc, CUtensorMap* tm, const void* p, int d0, int d1, int d2, long s1, long s2, int b0, int b1, int b2,
                     CUtensorMapSwizzle sw, CUtensorMapL2promotion pr) {
  cuuint64_t gd[3] = {(cuuint64_t)d0, (cuuint64_t)d1, (cuuint64_t)d2}, gs[2] = {(cuuint64_t)s1 * 2, (cuuint64_t)s2 * 2};
  cuuint32_t bd[3] = {(cuuint32_t)b0, (cuuint32_t)b1, (cuuint32_t)b2}, es[3] = {1, 1, 1};
  enc(tm, CU_TENSOR_MAP_DATA_TYPE_BFLOAT16, 3, (void*)p, gd, gs, bd, es, CU_TENSOR_MAP_INTERLEAVE_NONE, sw, pr, CU_TENSOR_MAP_FLOAT_OOB_FILL_NONE);
}

extern "C" void kernel_launch(void* const* d_in, const int* in_sizes, int n_in, void* d_out, int out_size) {
  Params P;
  P.x = (const bf16*)d_in[0]; P.logA = (const bf16*)d_in[1]; P.Aim = (const bf16*)d_in[2]; P.Cre = (const bf16*)d_in[3]; P.Cim = (const bf16*)d_in[4];
  P.logdt = (const bf16*)d_in[5]; P.Dsk = (const bf16*)d_in[6];
  P.wg = (const bf16*)d_in[8]; P.wu = (const bf16*)d_in[9]; P.wd = (const bf16*)d_in[10];
  P.c = (const bf16*)d_in[11]; P.wmod = (const bf16*)d_in[12]; P.out = (bf16*)d_out;
  {
    int cnt[4] = {0, 0, 0, 0};
    for (int c = 0; c < 64; c++) {
      const int gpc = c < 4 ? 0 : (c < 36 ? (c - 4) % 8 : 1 + (c - 36) % 7);
      const int q = gpc == 0 ? 3 : (gpc - 1) >> 1;
      P.tile[c] = (unsigned char)(cnt[q]++ << 2 | q);
    }
  }
  {
    static const int stage[12] = {1, 1, 1, 2, 0, 2, 0, 2, 1, 1, 1, 2}, atom[12] = {0, 1, 2, 0, 0, 1, 1, 2, 0, 1, 2, 0};
    static const int step[16] = {0, 1, 2, 3, 4, 5, 6, 3, 4, 5, 6, 7, 8, 9, 10, 11}, what[16] = {3, 3, 3, 1, 1, 1, 1, 2, 2, 2, 2, 3, 3, 3, 3, 3};
    static const int grp[16] = {0, 0, 0, 1, 1, 2, 2, 3, 3, 3, 3, 3, 4, 4, 4, 5};
    static const int wt[6] = {B_EMPTY + 8, B_AE, B_AE + 8, B_EMPTY + 16, B_EMPTY + 8, B_EMPTY + 16}, fl[6] = {B_FULL + 8, B_WF, B_WF + 8, B_FULL + 16, B_FULL + 8, B_FULL + 16};
    static const int kb4[6] = {15, 8, 8, 9, 15, 5};
    for (int n = 0; n < 12; n++) P.slot[n] = make_uint2(stage[n] * 4096 + 1024 + atom[n] * 512, stage[n] * 4096 + atom[n] * 256);
    for (int i = 0; i < 16; i++) {
      const int n = step[i], gq = grp[i];
      P.job[i] = make_uint4(wt[gq] | (gq >= 4) << 8 | fl[gq] << 16, (i == 0 || grp[i - 1] != gq) ? kb4[gq] * 4096 : 0,
                            (what[i] & 1 ? stage[n] * 64 + 16 + atom[n] * 8 : 0xffff) | (unsigned)(what[i] & 2 ? stage[n] * 64 + atom[n] * 4 : 0xffff) << 16,
                            n < 3 ? 64 * n : (n % 3 + 1) << 8 | 64 * (n / 3 - 1));
    }
  }
  void* fn = nullptr; cudaDriverEntryPointQueryResult qr;
  cudaGetDriverEntryPoint("cuTensorMapEncodeTiled", &fn, cudaEnableDefault, &qr);
  EncFn enc = (EncFn)fn;
  void *p_a, *p_x2, *p_in;
  cudaGetSymbolAddress(&p_a, g_aT); cudaGetSymbolAddress(&p_x2, g_x2T); cudaGetSymbolAddress(&p_in, g_in);
  Maps MP;
  const CUtensorMapSwizzle S0 = CU_TENSOR_MAP_SWIZZLE_NONE, S64 = CU_TENSOR_MAP_SWIZZLE_64B, S128 = CU_TENSOR_MAP_SWIZZLE_128B;
  const CUtensorMapL2promotion P0 = CU_TENSOR_MAP_L2_PROMOTION_NONE, P128 = CU_TENSOR_MAP_L2_PROMOTION_L2_128B, P256 = CU_TENSOR_MAP_L2_PROMOTION_L2_256B;
  make_map(enc, &tmM, d_in[12], 6 * D, 160, 4, 6 * D, 160L * 6 * D, 32, 160, 4, S64, WPROM);
  make_map(enc, &tmA, p_a, 64, D, L / 64, L, 64, 64, 64, 2, S128, P128);
  make_map(enc, &tmG, P.wg, 64, D, F / 64, F, 64, 64, 64, 3, S128, P256);
  make_map(enc, &tmU, P.wu, 64, D, F / 64, F, 64, 64, 64, 3, S128, P256);
  make_map(enc, &tmD, P.wd, 64, F, D / 64, D, 64, 64, 64, 1, S128, P256);
  make_map(enc, &tmD2, P.wd, 32, F, D / 32, D, 32, 32, 64, 1, S64, P0);
  make_map(enc, &tmX, p_x2, 64, D, L / 64, L, 64, 64, 64, 2, S128, P128);
  make_map(enc, &tmX2, p_x2, 64, D, L / 64, L, 64, 64, 16, 2, S128, P128);
  make_map(enc, &tmI, p_in, D * 16, 128, 1, D * 16, 128L * D * 16, 80, 128, 1, S0, P0);
  make_map(enc, &MP.m[7], P.wg, 64, D, F / 64, F, 64, 64, 256, 1, S128, P256);
  make_map(enc, &MP.m[8], P.wu, 64, D, F / 64, F, 64, 64, 256, 1, S128, P256);
  make_map(enc, &MP.m[11], P.wg, 64, D, F / 64, F, 64, 64, 64, 1, S128, P256);
  make_map(enc, &MP.m[12], P.wu, 64, D, F / 64, F, 64, 64, 64, 1, S128, P256);
  cudaFuncSetAttribute(mega, cudaFuncAttributeMaxDynamicSharedMemorySize, SM_TOTAL);
  const int grid = 128;
  mega<<<grid, 384, SM_TOTAL, cudaStreamPerThread>>>(P, MP);
}
```
